```python
import torch

def _softmax(x, axis=-1):
    return torch.softmax(x, dim=axis)
def _gelu(x):
    return torch.nn.functional.gelu(x, approximate="tanh")
def _silu(x):
    return torch.nn.functional.silu(x)
def _sigmoid(x):
    return torch.sigmoid(x)
def _layernorm(x, axis=-1, eps=1e-5):
    m = x.mean(dim=axis, keepdim=True)
    v = x.var(dim=axis, keepdim=True, unbiased=False)
    return (x - m) / torch.sqrt(v + eps)
def _scatter_add(tgt, idx, src, axis=0):
    return tgt.clone().index_add_(axis, idx, src)
def _segment_sum(src, seg, n):
    out = torch.zeros((n,) + src.shape[1:], dtype=src.dtype)
    return out.index_add_(0, seg, src)
def _pad(x, pw):
    flat = tuple(v for pair in reversed(pw) for v in pair)
    return torch.nn.functional.pad(x, flat)

kernel_name = 'sequential_preLN__sliding_block__moe_arch_mod__prompt'

def setup_inputs():

    _w = (lambda a: (lambda t: t.to(torch.bfloat16) if t.is_floating_point() else t)(torch.as_tensor(a)))
    def _A_setup():
        B, S, D = 1, 2048, 448
        return {
            "x": _w((lambda *s: torch.randn(*s, dtype=torch.bfloat16) * 0.05)(B, S, D)),
            "wqkv": _w((lambda *s: torch.randn(*s, dtype=torch.bfloat16) * 0.05)(D, 3 * D)),
            "wo": _w((lambda *s: torch.randn(*s, dtype=torch.bfloat16) * 0.05)(D, D)),
        }
    _A_in = _A_setup()

    def _B_setup():
        B, S, D, F, C = 1, 2048, 448, 1792, 2
        return {
            "x": _w((lambda *s: torch.randn(*s, dtype=torch.bfloat16) * 0.05)(B, S, D)),
            "w_r": _w((lambda *s: torch.randn(*s, dtype=torch.bfloat16) * 0.05)(D)),
            "w_gate": _w((lambda *s: torch.randn(*s, dtype=torch.bfloat16) * 0.05)(D, F)),
            "w_up": _w((lambda *s: torch.randn(*s, dtype=torch.bfloat16) * 0.05)(D, F)),
            "w_down": _w((lambda *s: torch.randn(*s, dtype=torch.bfloat16) * 0.05)(F, D)),
        }
    _B_in = _B_setup()

    return {
        "A_x": _A_in["x"],
        "A_wqkv": _A_in["wqkv"],
        "A_wo": _A_in["wo"],
        "B_x": _B_in["x"],
        "B_w_r": _B_in["w_r"],
        "B_w_gate": _B_in["w_gate"],
        "B_w_up": _B_in["w_up"],
        "B_w_down": _B_in["w_down"],
    }

def reference(A_x, A_wqkv, A_wo, B_x, B_w_r, B_w_gate, B_w_up, B_w_down):
    def _A_ref(x, wqkv, wo):
        B, S, D = x.shape
        H = 16; Dh = D // H; W = 256
        qkv = (lambda x, *d: x.permute(*d))((x @ wqkv).reshape(B, S, 3, H, Dh), 2, 0, 3, 1, 4)
        q, k, v = qkv[0], qkv[1], qkv[2]
        scores = torch.einsum("bhqd,bhkd->bhqk", q, k) * (Dh ** -0.5)
        idx = torch.arange(S)
        mask = (idx[:, None] - idx[None, :] >= 0) & (idx[:, None] - idx[None, :] < W)
        scores = torch.where(mask[None, None], scores, -1e9)
        p = _softmax(scores, axis=-1)
        o = torch.einsum("bhqk,bhkd->bhqd", p, v)
        return (lambda x, *d: x.permute(*d))(o, 0, 2, 1, 3).reshape(B, S, D) @ wo

    def _B_ref(x, w_r, w_gate, w_up, w_down):
        B, S, D = x.shape
        C = 2
        r = x @ w_r
        idx = torch.argsort(-r, axis=-1)[:, :C]
        idx_e = (lambda x, n, axis: torch.repeat_interleave(x, n, dim=axis))(idx.reshape(B, C, 1), D, axis=2)
        x_sel = (lambda x, i, axis: torch.take_along_dim(x, i, dim=axis))(x, idx_e, axis=1)
        g = _silu(x_sel @ w_gate)
        u = x_sel @ w_up
        y = (g * u) @ w_down
        r_sel = _sigmoid((lambda x, i, axis: torch.take_along_dim(x, i, dim=axis))(r, idx, axis=1))
        y = y * r_sel.reshape(B, C, 1)
        b_off = (torch.arange(B) * S).reshape(B, 1)
        flat_idx = (idx + b_off).reshape(B * C)
        zero = (x * 0.0).reshape(B * S, D)
        upd = _scatter_add(zero, flat_idx, y.reshape(B * C, D), axis=0)
        return x + upd.reshape(B, S, D)

    x = A_x
    h = x + _A_ref(_layernorm(x, axis=-1), A_wqkv, A_wo)
    h2 = h + _B_ref(_layernorm(h, axis=-1), B_w_r, B_w_gate, B_w_up, B_w_down)
    return h2
```

```cpp
#include <cuda_runtime.h>
#include <cuda_bf16.h>
#include <cuda.h>
#include <stdint.h>

namespace {

constexpr int D_ = 448, F_ = 1792, S_ = 2048;
constexpr int NCTA = 128, NTHR = 384;

constexpr uint32_t OFF_WK = 0;
constexpr uint32_t OFF_X = 57344;
constexpr uint32_t OFF_KA = 57344;
constexpr uint32_t OFF_XR = 100352;
constexpr uint32_t OFF_WQ = 114688;
constexpr uint32_t OFF_WV = 172032;
constexpr uint32_t OFF_BAR = 229376;
constexpr uint32_t OFF_MISC = OFF_BAR + 512;
constexpr uint32_t SMEM_BYTES = 232448;
constexpr uint32_t OFF_VA = 0;
constexpr uint32_t OFF_EX = 0;
constexpr uint32_t OFF_RED = 28672;
constexpr uint32_t OFF_RED2 = 32768;
constexpr uint32_t OFF_WG = OFF_KA, OFF_WU = OFF_KA + 14336, OFF_WD = OFF_KA + 28672;

enum { B_XF = 0, B_WKF = 7, B_WVF = 14, B_WQF = 15, B_XE = 16, B_KPD = 17, B_VPD = 18, B_QPD = 19,
       B_KB = 20, B_VB = 26, B_WOF = 32, B_XRF = 34, B_ATD = 35, B_FFW = 36, B_TOP = 37, B_E3D = 38, B_SW = 39,
       B_COUNT = 40 };

__device__ uint32_t g_epoch;
__device__ uint4 g_kv[NCTA * 2 * 2 * 5 * 128];
__device__ uint4 g_o[NCTA * 2 * 2 * 3 * 128];
__device__ uint4 g_st[32 * 8 * 64];
__device__ uint4 g_top[128 * 2];
__device__ uint4 g_cand[S_ * 8 * 6 * 4];
__device__ uint4 g_y[112 * 256];
#define TS(i)

__device__ __forceinline__ void spin_guard(int& n) {
  if (++n > (1 << 21)) __trap();
}
__device__ __forceinline__ void mbar_init(uint32_t bar, uint32_t cnt) {
  asm volatile("mbarrier.init.shared::cta.b64 [%0], %1;" ::"r"(bar), "r"(cnt) : "memory");
}
__device__ __forceinline__ void mbar_expect(uint32_t bar, uint32_t bytes) {
  asm volatile("mbarrier.arrive.expect_tx.shared::cta.b64 _, [%0], %1;" ::"r"(bar), "r"(bytes) : "memory");
}
__device__ __forceinline__ void mbar_arrive(uint32_t bar) {
  asm volatile("mbarrier.arrive.shared::cta.b64 _, [%0];" ::"r"(bar) : "memory");
}
__device__ __forceinline__ void mbar_wait(uint32_t bar) {
  asm volatile("{\n.reg .pred p;\n.reg .u32 n;\nmov.u32 n, 0;\nMW_LOOP:\n"
               "mbarrier.try_wait.parity.shared::cta.b64 p, [%0], 0, 2000;\n@p bra MW_DONE;\n"
               "add.u32 n, n, 1;\nsetp.lt.u32 p, n, 1048576;\n@p bra MW_LOOP;\ntrap;\nMW_DONE:\n}" ::"r"(bar) : "memory");
}
__device__ __forceinline__ void warp_arrive(uint32_t bar, int lane) {
  __syncwarp();
  if (lane == 0) mbar_arrive(bar);
}
__device__ __forceinline__ void fence_async() { asm volatile("fence.proxy.async.shared::cta;" ::: "memory"); }
__device__ __forceinline__ void tma2d(uint32_t dst, const CUtensorMap* m, int c0, int c1, uint32_t bar) {
  asm volatile("cp.async.bulk.tensor.2d.shared::cluster.global.mbarrier::complete_tx::bytes [%0], [%1, {%3, %4}], [%2];"
               ::"r"(dst), "l"(m), "r"(bar), "r"(c0), "r"(c1) : "memory");
}
__device__ __forceinline__ void bulk_g2s(uint32_t dst, const void* src, uint32_t bytes, uint32_t bar) {
  asm volatile("cp.async.bulk.shared::cluster.global.mbarrier::complete_tx::bytes [%0], [%1], %2, [%3];"
               ::"r"(dst), "l"(src), "r"(bytes), "r"(bar) : "memory");
}
__device__ __forceinline__ void bulk_s2g(void* dst, uint32_t src, uint32_t bytes) {
  asm volatile("cp.async.bulk.global.shared::cta.bulk_group [%0], [%1], %2;" ::"l"(dst), "r"(src), "r"(bytes) : "memory");
}
__device__ __forceinline__ void l2_prefetch(const void* p, uint32_t bytes) {
  asm volatile("cp.async.bulk.prefetch.L2.global [%0], %1;" ::"l"(p), "r"(bytes) : "memory");
}
__device__ __forceinline__ void st_pkt(uint4* p, uint32_t a, uint32_t b, uint32_t c, uint32_t d) {
  asm volatile("st.relaxed.gpu.global.v4.u32 [%0], {%1, %2, %3, %4};" ::"l"(p), "r"(a), "r"(b), "r"(c), "r"(d) : "memory");
}
__device__ __forceinline__ uint4 ld_pkt(const uint4* p) {
  uint4 v;
  asm volatile("ld.relaxed.gpu.global.v4.u32 {%0, %1, %2, %3}, [%4];" : "=r"(v.x), "=r"(v.y), "=r"(v.z), "=r"(v.w) : "l"(p) : "memory");
  return v;
}
__device__ __forceinline__ uint32_t ld_tag(const uint4* p) {
  uint32_t v;
  asm volatile("ld.relaxed.gpu.global.u32 %0, [%1+12];" : "=r"(v) : "l"(p) : "memory");
  return v;
}
__device__ __forceinline__ void ldsm4(uint32_t& r0, uint32_t& r1, uint32_t& r2, uint32_t& r3, uint32_t a) {
  asm volatile("ldmatrix.sync.aligned.m8n8.x4.shared.b16 {%0,%1,%2,%3}, [%4];"
               : "=r"(r0), "=r"(r1), "=r"(r2), "=r"(r3) : "r"(a) : "memory");
}
__device__ __forceinline__ void ldsm4t(uint32_t& r0, uint32_t& r1, uint32_t& r2, uint32_t& r3, uint32_t a) {
  asm volatile("ldmatrix.sync.aligned.m8n8.x4.trans.shared.b16 {%0,%1,%2,%3}, [%4];"
               : "=r"(r0), "=r"(r1), "=r"(r2), "=r"(r3) : "r"(a) : "memory");
}
__device__ __forceinline__ void ldsm2t(uint32_t& r0, uint32_t& r1, uint32_t a) {
  asm volatile("ldmatrix.sync.aligned.m8n8.x2.trans.shared.b16 {%0,%1}, [%2];" : "=r"(r0), "=r"(r1) : "r"(a) : "memory");
}
__device__ __forceinline__ void stsm4(uint32_t a, uint32_t r0, uint32_t r1, uint32_t r2, uint32_t r3) {
  asm volatile("stmatrix.sync.aligned.m8n8.x4.shared.b16 [%0], {%1,%2,%3,%4};" ::"r"(a), "r"(r0), "r"(r1), "r"(r2), "r"(r3) : "memory");
}
__device__ __forceinline__ void stsm2(uint32_t a, uint32_t r0, uint32_t r1) {
  asm volatile("stmatrix.sync.aligned.m8n8.x2.shared.b16 [%0], {%1,%2};" ::"r"(a), "r"(r0), "r"(r1) : "memory");
}
__device__ __forceinline__ void mma16816(float (&c)[4], uint32_t a0, uint32_t a1, uint32_t a2, uint32_t a3, uint32_t b0, uint32_t b1) {
  asm volatile("mma.sync.aligned.m16n8k16.row.col.f32.bf16.bf16.f32 {%0,%1,%2,%3}, {%4,%5,%6,%7}, {%8,%9}, {%0,%1,%2,%3};"
               : "+f"(c[0]), "+f"(c[1]), "+f"(c[2]), "+f"(c[3]) : "r"(a0), "r"(a1), "r"(a2), "r"(a3), "r"(b0), "r"(b1));
}
__device__ __forceinline__ void mma1688(float (&c)[4], uint32_t a0, uint32_t a1, uint32_t b0) {
  asm volatile("mma.sync.aligned.m16n8k8.row.col.f32.bf16.bf16.f32 {%0,%1,%2,%3}, {%4,%5}, {%6}, {%0,%1,%2,%3};"
               : "+f"(c[0]), "+f"(c[1]), "+f"(c[2]), "+f"(c[3]) : "r"(a0), "r"(a1), "r"(b0));
}
__device__ __forceinline__ uint32_t pack2(float lo, float hi) {
  uint32_t r;
  asm("cvt.rn.bf16x2.f32 %0, %1, %2;" : "=r"(r) : "f"(hi), "f"(lo));
  return r;
}
__device__ __forceinline__ float bf_lo(uint32_t u) { return __uint_as_float(u << 16); }
__device__ __forceinline__ float bf_hi(uint32_t u) { return __uint_as_float(u & 0xffff0000u); }
__device__ __forceinline__ float bfr(float x) { return bf_lo(pack2(x, 0.f)); }
__device__ __forceinline__ uint32_t hsub2(uint32_t a, uint32_t b) {
  uint32_t r;
  asm("sub.rn.bf16x2 %0, %1, %2;" : "=r"(r) : "r"(a), "r"(b));
  return r;
}
__device__ __forceinline__ uint32_t hadd2(uint32_t a, uint32_t b) {
  uint32_t r;
  asm("add.rn.bf16x2 %0, %1, %2;" : "=r"(r) : "r"(a), "r"(b));
  return r;
}
__device__ __forceinline__ float ex2(float x) {
  float r;
  asm("ex2.approx.ftz.f32 %0, %1;" : "=f"(r) : "f"(x));
  return r;
}
__device__ __forceinline__ uint32_t lds32(uint32_t a) {
  uint32_t v;
  asm volatile("ld.shared.u32 %0, [%1];" : "=r"(v) : "r"(a) : "memory");
  return v;
}
__device__ __forceinline__ void sts32(uint32_t a, uint32_t v) { asm volatile("st.shared.u32 [%0], %1;" ::"r"(a), "r"(v) : "memory"); }
__device__ __forceinline__ void sts64f(uint32_t a, float x, float y) {
  asm volatile("st.shared.v2.f32 [%0], {%1,%2};" ::"r"(a), "f"(x), "f"(y) : "memory");
}
__device__ __forceinline__ void sts128f(uint32_t a, float x, float y, float z, float w) {
  asm volatile("st.shared.v4.f32 [%0], {%1,%2,%3,%4};" ::"r"(a), "f"(x), "f"(y), "f"(z), "f"(w) : "memory");
}
__device__ __forceinline__ float4 lds128f(uint32_t a) {
  float4 v;
  asm volatile("ld.shared.v4.f32 {%0,%1,%2,%3}, [%4];" : "=f"(v.x), "=f"(v.y), "=f"(v.z), "=f"(v.w) : "r"(a) : "memory");
  return v;
}
__device__ __forceinline__ void bar_sync(int id, int n) { asm volatile("bar.sync %0, %1;" ::"r"(id), "r"(n) : "memory"); }
__device__ __forceinline__ void bar_arrive(int id, int n) { asm volatile("bar.arrive %0, %1;" ::"r"(id), "r"(n) : "memory"); }
__device__ __forceinline__ uint64_t mkdesc(uint32_t addr, uint32_t lbo, uint32_t sbo, uint32_t sw) {
  return (uint64_t)((addr & 0x3FFFF) >> 4) | ((uint64_t)(lbo >> 4) << 16) | ((uint64_t)(sbo >> 4) << 32) | ((uint64_t)sw << 62);
}
#define WG_FENCE() asm volatile("wgmma.fence.sync.aligned;" ::: "memory")
#define WG_COMMIT() asm volatile("wgmma.commit_group.sync.aligned;" ::: "memory")
#define WG_WAIT(n) asm volatile("wgmma.wait_group.sync.aligned " #n ";" ::: "memory")
template <int N> __device__ __forceinline__ void pin(float (&d)[N]) {
#pragma unroll
  for (int i = 0; i < N; i++) asm volatile("" : "+f"(d[i])::"memory");
}

#define R4(d, i) "+f"(d[i]), "+f"(d[i + 1]), "+f"(d[i + 2]), "+f"(d[i + 3])
__device__ __forceinline__ void wg40(float (&d)[20], uint32_t a0, uint32_t a1, uint32_t a2, uint32_t a3, uint64_t b) {
  asm volatile("wgmma.mma_async.sync.aligned.m64n40k16.f32.bf16.bf16 "
               "{%0,%1,%2,%3,%4,%5,%6,%7,%8,%9,%10,%11,%12,%13,%14,%15,%16,%17,%18,%19}, {%20,%21,%22,%23}, %24, 1, 1, 1, 1;"
               : R4(d, 0), R4(d, 4), R4(d, 8), R4(d, 12), R4(d, 16) : "r"(a0), "r"(a1), "r"(a2), "r"(a3), "l"(b));
}
template <int ACC> __device__ __forceinline__ void wg56(float (&d)[28], uint32_t a0, uint32_t a1, uint32_t a2, uint32_t a3, uint64_t b) {
  asm volatile("wgmma.mma_async.sync.aligned.m64n56k16.f32.bf16.bf16 "
               "{%0,%1,%2,%3,%4,%5,%6,%7,%8,%9,%10,%11,%12,%13,%14,%15,%16,%17,%18,%19,%20,%21,%22,%23,%24,%25,%26,%27}, "
               "{%28,%29,%30,%31}, %32, %33, 1, 1, 1;"
               : R4(d, 0), R4(d, 4), R4(d, 8), R4(d, 12), R4(d, 16), R4(d, 20), R4(d, 24)
               : "r"(a0), "r"(a1), "r"(a2), "r"(a3), "l"(b), "n"(ACC));
}
template <int ACC> __device__ __forceinline__ void wg64(float (&d)[32], uint32_t a0, uint32_t a1, uint32_t a2, uint32_t a3, uint64_t b) {
  asm volatile("wgmma.mma_async.sync.aligned.m64n64k16.f32.bf16.bf16 "
               "{%0,%1,%2,%3,%4,%5,%6,%7,%8,%9,%10,%11,%12,%13,%14,%15,%16,%17,%18,%19,%20,%21,%22,%23,%24,%25,%26,%27,%28,%29,%30,%31}, "
               "{%32,%33,%34,%35}, %36, %37, 1, 1, 0;"
               : R4(d, 0), R4(d, 4), R4(d, 8), R4(d, 12), R4(d, 16), R4(d, 20), R4(d, 24), R4(d, 28)
               : "r"(a0), "r"(a1), "r"(a2), "r"(a3), "l"(b), "n"(ACC));
}
template <int ACC> __device__ __forceinline__ void wg112(float (&d)[56], uint32_t a0, uint32_t a1, uint32_t a2, uint32_t a3, uint64_t b) {
  asm volatile("wgmma.mma_async.sync.aligned.m64n112k16.f32.bf16.bf16 "
               "{%0,%1,%2,%3,%4,%5,%6,%7,%8,%9,%10,%11,%12,%13,%14,%15,%16,%17,%18,%19,%20,%21,%22,%23,%24,%25,%26,%27,"
               "%28,%29,%30,%31,%32,%33,%34,%35,%36,%37,%38,%39,%40,%41,%42,%43,%44,%45,%46,%47,%48,%49,%50,%51,%52,%53,%54,%55}, "
               "{%56,%57,%58,%59}, %60, %61, 1, 1, 1;"
               : R4(d, 0), R4(d, 4), R4(d, 8), R4(d, 12), R4(d, 16), R4(d, 20), R4(d, 24), R4(d, 28), R4(d, 32), R4(d, 36),
                 R4(d, 40), R4(d, 44), R4(d, 48), R4(d, 52)
               : "r"(a0), "r"(a1), "r"(a2), "r"(a3), "l"(b), "n"(ACC));
}

__device__ __forceinline__ float ln_rstd(float var) {
  float s = bfr(sqrtf(bfr(bfr(fmaxf(var, 0.f)) + 1e-5f)));
  return 1.0f / s;
}
__device__ __forceinline__ void store_image(uint32_t img, const uint32_t (&e)[15], int v, int lane) {
  uint32_t a = img + (lane >> 4) * 1024 + (16 * v + ((lane >> 3) & 1) * 8 + (lane & 7)) * 16;
  stsm4(a, e[0], e[1], e[2], e[3]);
  stsm4(a + 2048, e[4], e[5], e[6], e[7]);
  stsm4(a + 4096, e[8], e[9], e[10], e[11]);
  stsm2(a + 6144, e[12], e[13]);
}
__device__ __forceinline__ void kv_epilogue(const float (&acc)[28], float rs0, float rs1, uint32_t img, uint4* gp, uint32_t epoch,
                                            uint32_t bar, int v, int lane) {
  uint32_t e[15];
#pragma unroll
  for (int j = 0; j < 7; j++) {
    e[2 * j] = pack2(acc[4 * j] * rs0, acc[4 * j + 1] * rs0);
    e[2 * j + 1] = pack2(acc[4 * j + 2] * rs1, acc[4 * j + 3] * rs1);
  }
  e[14] = 0;
#pragma unroll
  for (int i = 0; i < 5; i++) st_pkt(gp + i * 128, e[3 * i], e[3 * i + 1], e[3 * i + 2], epoch);
  store_image(img, e, v, lane);
  fence_async();
  warp_arrive(bar, lane);
}

constexpr float SC = 0.18898223650461361f * 1.4426950408889634f;

__device__ __forceinline__ void softmax_unit(float (&s)[32], bool present, float& m0, float& m1, float& al0, float& al1,
                                             uint32_t (&p)[16]) {
  float x0 = fmaxf(s[0], s[1]), x1 = fmaxf(s[2], s[3]);
#pragma unroll
  for (int j = 1; j < 8; j++) {
    x0 = fmaxf(x0, fmaxf(s[4 * j], s[4 * j + 1]));
    x1 = fmaxf(x1, fmaxf(s[4 * j + 2], s[4 * j + 3]));
  }
  x0 = fmaxf(x0, __shfl_xor_sync(~0u, x0, 1));
  x1 = fmaxf(x1, __shfl_xor_sync(~0u, x1, 1));
  x0 = fmaxf(x0, __shfl_xor_sync(~0u, x0, 2));
  x1 = fmaxf(x1, __shfl_xor_sync(~0u, x1, 2));
  float n0 = present ? fmaxf(m0, x0) : m0, n1 = present ? fmaxf(m1, x1) : m1;
  al0 = ex2((m0 - n0) * SC);
  al1 = ex2((m1 - n1) * SC);
  m0 = n0;
  m1 = n1;
  const float inf = __int_as_float(0x7f800000);
  float b0 = present ? -n0 * SC : -inf, b1 = present ? -n1 * SC : -inf;
#pragma unroll
  for (int j = 0; j < 8; j++) {
    p[2 * j] = pack2(ex2(fmaf(s[4 * j], SC, b0)), ex2(fmaf(s[4 * j + 1], SC, b0)));
    p[2 * j + 1] = pack2(ex2(fmaf(s[4 * j + 2], SC, b1)), ex2(fmaf(s[4 * j + 3], SC, b1)));
  }
}
__device__ __forceinline__ void rescale(float (&o)[20], float al0, float al1) {
#pragma unroll
  for (int j = 0; j < 5; j++) {
    o[4 * j] *= al0; o[4 * j + 1] *= al0; o[4 * j + 2] *= al1; o[4 * j + 3] *= al1;
  }
}
__device__ __forceinline__ void qk(float (&s)[32], const uint32_t (&q)[8], uint64_t kd) {
  wg64<0>(s, q[0], q[1], q[2], q[3], kd);
  wg64<1>(s, q[4], q[5], q[6], q[7], kd + 128);
}
__device__ __forceinline__ void pv(float (&o)[20], const uint32_t (&p)[16], uint64_t vd) {
#pragma unroll
  for (int k = 0; k < 4; k++) wg40(o, p[4 * k], p[4 * k + 1], p[4 * k + 2], p[4 * k + 3], vd + 16 * k);
}

struct Params {
  const __nv_bfloat16* wqkv; const __nv_bfloat16* wo; const __nv_bfloat16* wr;
  const __nv_bfloat16* wg; const __nv_bfloat16* wu; const __nv_bfloat16* wd;
  __nv_bfloat16* out;
};

__global__ void __launch_bounds__(NTHR, 1)
fused_kernel(const __grid_constant__ CUtensorMap tm_x, const __grid_constant__ CUtensorMap tm_w,
             const __grid_constant__ CUtensorMap tm_wo, const __grid_constant__ CUtensorMap tm_xr,
             const __grid_constant__ CUtensorMap tm_g, const __grid_constant__ CUtensorMap tm_u, const Params P) {
  extern __shared__ __align__(1024) unsigned char smem_raw[];
  const uint32_t sb = (uint32_t)__cvta_generic_to_shared(smem_raw);
  const uint32_t bars = sb + OFF_BAR;
#define BAR(i) (bars + 8 * (i))
  const int tid = threadIdx.x, warp = tid >> 5, lane = tid & 31;
  const int bid = blockIdx.x;
  const int rb = (bid >> 5) * 4 + ((bid >> 2) & 3), hg = ((bid >> 4) & 1) * 4 + (bid & 3);
  const int half = hg >> 2, quart = hg & 3;

  if (warp == 8) {
    for (int i = lane; i < B_COUNT; i += 32) {
      uint32_t cnt = 1;
      if (i == B_XE || i == B_KPD || i == B_VPD || i == B_QPD || i == B_ATD || i == B_VB + 4 || i == B_VB + 5) cnt = 8;
      else if (i >= B_KB && i < B_VB + 4) cnt = 4;
      mbar_init(BAR(i), cnt);
    }
    asm volatile("fence.mbarrier_init.release.cluster;" ::: "memory");
    fence_async();
    __syncwarp();
    bar_arrive(0, NTHR);
  } else {
    bar_sync(0, NTHR);
  }
  uint32_t epoch;
  asm volatile("ld.relaxed.gpu.global.u32 %0, [%1];" : "=r"(epoch) : "l"(&g_epoch) : "memory");

  if (warp >= 8) {
    asm volatile("setmaxnreg.dec.sync.aligned.u32 56;");
    const int t = tid - 256, aw = warp - 8;
    const int wcol = ((hg * 112) & ~31) >> 1;
    if (t == 0) {
      for (int i = 0; i < 7; i++) {
        mbar_expect(BAR(B_XF + i), 16384);
        tma2d(sb + OFF_X + i * 16384, &tm_x, i * 64, rb * 128, BAR(B_XF + i));
      }
      for (int i = 0; i < 7; i++) {
        mbar_expect(BAR(B_WKF + i), 8192);
        tma2d(sb + OFF_WK + i * 8192, &tm_w, 448 + wcol, i * 64, BAR(B_WKF + i));
      }
      mbar_expect(BAR(B_WVF), 57344);
      for (int i = 0; i < 7; i++) tma2d(sb + OFF_WV + i * 8192, &tm_w, 896 + wcol, i * 64, BAR(B_WVF));
      mbar_wait(BAR(B_XE));
      mbar_expect(BAR(B_WQF), 57344);
      for (int i = 0; i < 7; i++) tma2d(sb + OFF_WQ + i * 8192, &tm_w, wcol, i * 64, BAR(B_WQF));
      mbar_expect(BAR(B_XRF), 14336);
      tma2d(sb + OFF_XR, &tm_xr, quart * 112, rb * 128 + half * 64, BAR(B_XRF));
    } else if (aw == 1) {
      if (lane == 0) l2_prefetch((const char*)P.wqkv + bid * 9408, 9408);
      float s = 0.f;
      for (int i = lane; i < 224; i += 32) {
        uint32_t u = __ldg((const uint32_t*)P.wr + i);
        s += bf_lo(u) + bf_hi(u);
      }
      for (int o = 16; o; o >>= 1) s += __shfl_xor_sync(~0u, s, o);
      if (lane == 0) {
        sts32(sb + OFF_MISC + 16, __float_as_uint(s));
        mbar_arrive(BAR(B_SW));
        mbar_wait(BAR(B_XE));
        l2_prefetch((const char*)P.wo + bid * 3136, 3136);
        l2_prefetch((const char*)P.wg + bid * 12544, 12544);
        l2_prefetch((const char*)P.wu + bid * 12544, 12544);
        l2_prefetch((const char*)P.wd + bid * 12544, 12544);
      }
    }
    __syncwarp();
    epoch += 1;
    mbar_wait(BAR(B_KPD));
    for (int i = t; i < 7 * 64; i += 128)
      sts128f(sb + OFF_VA + (i >> 6) * 8192 + (i & 63) * 16, __uint_as_float(0x3f803f80u), __uint_as_float(0x3f803f80u),
              __uint_as_float(0x3f803f80u), __uint_as_float(0x3f803f80u));
    fence_async();
    __syncwarp();
    if (lane == 0) { mbar_arrive(BAR(B_VB + 4)); mbar_arrive(BAR(B_VB + 5)); }
    TS(0);
    for (int it = 0; it < 8; it++) {
      const int kv = it >> 2, s = ((it & 1) ? 0 : 2) + ((it >> 1) & 1);
      if (it == 4 && t == 0) {
        mbar_wait(BAR(B_VPD));
        mbar_expect(BAR(B_WOF + 1), 57344);
        tma2d(sb + OFF_WV, &tm_wo, quart * 112, 224, BAR(B_WOF + 1));
        tma2d(sb + OFF_WV + 28672, &tm_wo, quart * 112 + 64, 224, BAR(B_WOF + 1));
      }
      __syncwarp();
      if (2 * rb + s - 4 < 0) continue;
      const uint4* gp = g_kv + ((((rb - 2 + (s >> 1)) * 8 + hg) * 2 + kv) * 2 + (s & 1)) * 640 + t;
      int t0 = 0;
      if (lane == 0) while (ld_tag(gp + 512) != epoch) spin_guard(t0);
      __syncwarp();
      uint32_t e[15];
      while (true) {
        bool ok = true;
#pragma unroll
        for (int i = 0; i < 5; i++) {
          uint4 q = ld_pkt(gp + i * 128);
          e[3 * i] = q.x; e[3 * i + 1] = q.y; e[3 * i + 2] = q.z;
          ok &= (q.w == epoch);
        }
        if (__all_sync(~0u, ok)) break;
        spin_guard(t0);
      }
      store_image(kv ? sb + OFF_VA + s * 8192 + 1024 : sb + OFF_KA + s * 7168, e, aw, lane);
      fence_async();
      warp_arrive(BAR((kv ? B_VB : B_KB) + s), lane);
      TS(1 + it);
    }
    if (t == 0) {
      mbar_wait(BAR(B_QPD));
      mbar_expect(BAR(B_WOF), 57344);
      tma2d(sb + OFF_WQ, &tm_wo, quart * 112, 0, BAR(B_WOF));
      tma2d(sb + OFF_WQ + 28672, &tm_wo, quart * 112 + 64, 0, BAR(B_WOF));
      if (bid < 112) {
        mbar_wait(BAR(B_ATD));
        mbar_expect(BAR(B_FFW), 43008);
        tma2d(sb + OFF_WG, &tm_g, bid * 16, 0, BAR(B_FFW));
        tma2d(sb + OFF_WG + 7168, &tm_g, bid * 16, 224, BAR(B_FFW));
        tma2d(sb + OFF_WU, &tm_u, bid * 16, 0, BAR(B_FFW));
        tma2d(sb + OFF_WU + 7168, &tm_u, bid * 16, 224, BAR(B_FFW));
        bulk_g2s(sb + OFF_WD, (const char*)P.wd + bid * 14336, 14336, BAR(B_FFW));
      }
    } else if (aw == 1) {
      mbar_wait(BAR(B_E3D));
      uint32_t k1, k2;
      int t0 = 0;
      while (true) {
        bool ok = true;
        k1 = 0; k2 = 0;
#pragma unroll
        for (int i = 0; i < 4; i++) {
          uint4 q = ld_pkt(g_top + (lane + 32 * i) * 2);
          ok &= (q.w == epoch);
          k2 = max(max(k2, min(k1, q.x)), q.y);
          k1 = max(k1, q.x);
        }
        if (__all_sync(~0u, ok)) break;
        spin_guard(t0);
      }
      uint32_t K1 = __reduce_max_sync(~0u, k1);
      uint32_t K2 = __reduce_max_sync(~0u, k1 == K1 ? k2 : k1);
      if (lane == 0) {
        sts32(sb + OFF_MISC, K1);
        sts32(sb + OFF_MISC + 4, K2);
        mbar_arrive(BAR(B_TOP));
        if (bid == 0) asm volatile("st.relaxed.gpu.global.u32 [%0], %1;" ::"l"(&g_epoch), "r"(epoch) : "memory");
      }
    }
  } else {
    asm volatile("setmaxnreg.inc.sync.aligned.u32 224;");
    const int w = warp >> 2, v = warp & 3, r = lane >> 2, c = lane & 3, wt = tid & 127;
    uint32_t qa[8], qb[8];
    {
      uint32_t a[112];
      float su[4] = {0.f, 0.f, 0.f, 0.f}, g0[4] = {0.f, 0.f, 0.f, 0.f}, g1[4] = {0.f, 0.f, 0.f, 0.f};
      const int xrow = 64 * w + 16 * v + (lane & 7) + ((lane >> 3) & 1) * 8;
      const uint32_t xa = sb + OFF_X + xrow * 128;
#pragma unroll
      for (int kc = 0; kc < 7; kc++) {
        mbar_wait(BAR(B_XF + kc));
#pragma unroll
        for (int s = 0; s < 4; s++) {
          const int i = 16 * kc + 4 * s;
          ldsm4(a[i], a[i + 1], a[i + 2], a[i + 3], xa + kc * 16384 + (((2 * s + (lane >> 4)) ^ (lane & 7)) << 4));
        }
#pragma unroll
        for (int s = 0; s < 4; s++) {
          const int i = 16 * kc + 4 * s;
          mma16816(su, a[i], a[i + 1], a[i + 2], a[i + 3], 0x3f803f80u, 0x3f803f80u);
          mma16816(g0, a[i], a[i + 1], a[i + 2], a[i + 3], a[i], a[i + 2]);
          mma16816(g1, a[i], a[i + 1], a[i + 2], a[i + 3], a[i + 1], a[i + 3]);
        }
      }
      warp_arrive(BAR(B_XE), lane);
      TS(0);
      const float mu0 = su[0] * (1.f / D_), mu1 = su[2] * (1.f / D_);
      const uint32_t mb0 = pack2(mu0, mu0), mb1 = pack2(mu1, mu1);
      const int dsrc = (lane & ~3) | (r >> 1);
      const float q0 = __shfl_sync(~0u, (r & 1) ? g0[1] : g0[0], dsrc), q1 = __shfl_sync(~0u, (r & 1) ? g1[3] : g1[2], dsrc);
      const float rs0 = ln_rstd(q0 * (1.f / D_) - mu0 * mu0), rs1 = ln_rstd(q1 * (1.f / D_) - mu1 * mu1);
#pragma unroll
      for (int i = 0; i < 112; i++) a[i] = hsub2(a[i], (i & 1) ? mb1 : mb0);
      epoch += 1;

      const uint32_t wofs = (hg & 1) * 16;
      uint4* gp = g_kv + (((rb * 8 + hg) * 2) * 2 + w) * 640 + wt;
      float acc[28];
      if (w == 1) bar_sync(1, 256);
      {
        const uint64_t d = mkdesc(sb + OFF_WK + wofs, 16, 1024, 1);
        WG_FENCE();
#pragma unroll
        for (int kc = 0; kc < 7; kc++) {
          mbar_wait(BAR(B_WKF + kc));
#pragma unroll
          for (int s = 0; s < 4; s++) {
            const int k = 4 * kc + s;
            if (k == 0) wg56<0>(acc, a[0], a[1], a[2], a[3], d);
            else wg56<1>(acc, a[4 * k], a[4 * k + 1], a[4 * k + 2], a[4 * k + 3], d + 128 * k);
          }
        }
        WG_COMMIT();
        bar_arrive(w == 0 ? 1 : 2, 256);
        WG_WAIT(0);
        pin(acc);
        TS(1);
        warp_arrive(BAR(B_KPD), lane);
        mbar_wait(BAR(B_XE));
        kv_epilogue(acc, rs0, rs1, sb + OFF_KA + (4 + w) * 7168, gp, epoch, BAR(B_KB + 4 + w), v, lane);
      }
      {
        const uint64_t d = mkdesc(sb + OFF_WV + wofs, 16, 1024, 1);
        mbar_wait(BAR(B_WVF));
        bar_sync(w == 0 ? 2 : 1, 256);
        WG_FENCE();
#pragma unroll
        for (int k = 0; k < 28; k++) {
          if (k == 0) wg56<0>(acc, a[0], a[1], a[2], a[3], d);
          else wg56<1>(acc, a[4 * k], a[4 * k + 1], a[4 * k + 2], a[4 * k + 3], d + 128 * k);
        }
        WG_COMMIT();
        bar_arrive(w == 0 ? 1 : 2, 256);
        WG_WAIT(0);
        pin(acc);
        TS(2);
        warp_arrive(BAR(B_VPD), lane);
        mbar_wait(BAR(B_KPD));
        kv_epilogue(acc, rs0, rs1, sb + OFF_VA + (4 + w) * 8192 + 1024, gp + 2 * 640, epoch, BAR(B_VB + 4 + w), v, lane);
      }
      {
        const uint64_t d = mkdesc(sb + OFF_WQ + wofs, 16, 1024, 1);
        mbar_wait(BAR(B_WQF));
        bar_sync(w == 0 ? 2 : 1, 256);
        WG_FENCE();
#pragma unroll
        for (int k = 0; k < 28; k++) {
          if (k == 0) wg56<0>(acc, a[0], a[1], a[2], a[3], d);
          else wg56<1>(acc, a[4 * k], a[4 * k + 1], a[4 * k + 2], a[4 * k + 3], d + 128 * k);
        }
        WG_COMMIT();
        if (w == 0) bar_arrive(1, 256);
        WG_WAIT(0);
        pin(acc);
        TS(3);
        warp_arrive(BAR(B_QPD), lane);
        uint32_t e[14];
#pragma unroll
        for (int j = 0; j < 7; j++) {
          e[2 * j] = pack2(acc[4 * j] * rs0, acc[4 * j + 1] * rs0);
          e[2 * j + 1] = pack2(acc[4 * j + 2] * rs1, acc[4 * j + 3] * rs1);
        }
#pragma unroll
        for (int i = 0; i < 6; i++) { qa[i] = e[i]; qb[2 + i] = e[8 + i]; }
        qa[6] = c < 2 ? e[6] : 0u; qa[7] = c < 2 ? e[7] : 0u;
        qb[0] = c < 2 ? 0u : e[6]; qb[1] = c < 2 ? 0u : e[7];
      }
    }

    {
      const int lo = 4 - 2 * rb;
      const int s0 = w ? 4 : 2, s1 = w ? 2 : 1, s2 = 3, sf = w, sd = w + 4;
      const bool p0 = s0 >= lo, p1 = s1 >= lo, p2 = s2 >= lo, pf = sf >= lo;
      const int e0 = p0 ? s0 : 4, e1 = p1 ? s1 : 4, e2 = p2 ? s2 : 4, ef = pf ? sf : 4;
      const int t0 = 16 * v + r - 2 * c;
      uint64_t kd = mkdesc(sb + OFF_KA, 1024, 128, 0), vd = mkdesc(sb + OFF_VA, 128, 1024, 0);
      uint4* op = g_o + ((rb * 8 + hg) * 2 + w) * 768 + wt;
      float sa[32], sbb[32], sc[32], o[20];
      uint32_t p[16], pd[16];
      mbar_wait(BAR(B_KB + e0));
      WG_FENCE();
      qk(sa, qa, kd + e0 * 448);
      WG_COMMIT();
#pragma unroll 1
      for (int hd = 0; hd < 2; hd++) {
        float m0 = -3.0e38f, m1 = -3.0e38f, al0, al1;
#pragma unroll
        for (int i = 0; i < 20; i++) o[i] = 0.f;
        mbar_wait(BAR(B_KB + e1));
        WG_FENCE();
        qk(sbb, qa, kd + e1 * 448);
        WG_COMMIT();
        WG_WAIT(1);
        pin(sa);
        softmax_unit(sa, p0, m0, m1, al0, al1, p);
        mbar_wait(BAR(B_VB + e0));
        mbar_wait(BAR(B_KB + e2));
        WG_FENCE();
        pv(o, p, vd + e0 * 512);
        WG_COMMIT();
        qk(sa, qa, kd + e2 * 448);
        WG_COMMIT();
        WG_WAIT(2);
        pin(sbb);
        softmax_unit(sbb, p1, m0, m1, al0, al1, pd);
        mbar_wait(BAR(B_VB + e1));
        mbar_wait(BAR(B_KB + ef));
        mbar_wait(BAR(B_KB + sd));
        WG_WAIT(1);
        pin(o);
        rescale(o, al0, al1);
        WG_FENCE();
        pv(o, pd, vd + e1 * 512);
        WG_COMMIT();
        qk(sbb, qa, kd + ef * 448);
        qk(sc, qa, kd + sd * 448);
        WG_COMMIT();
        WG_WAIT(2);
        pin(sa);
        softmax_unit(sa, p2, m0, m1, al0, al1, p);
        mbar_wait(BAR(B_VB + e2));
        WG_WAIT(1);
        pin(o);
        rescale(o, al0, al1);
        WG_FENCE();
        pv(o, p, vd + e2 * 512);
        WG_COMMIT();
        const uint64_t kdn = kd + 192;
        qk(sa, qb, kdn + e0 * 448);
        WG_COMMIT();
        WG_WAIT(2);
        pin(sbb);
        pin(sc);
        {
          const float ninf = __int_as_float(0xff800000);
#pragma unroll
          for (int j = 0; j < 8; j++) {
            const int t = t0 - 8 * j;
            sbb[4 * j] = t >= 0 ? sc[4 * j] : (pf ? sbb[4 * j] : ninf);
            sbb[4 * j + 1] = t >= 1 ? sc[4 * j + 1] : (pf ? sbb[4 * j + 1] : ninf);
            sbb[4 * j + 2] = t >= -8 ? sc[4 * j + 2] : (pf ? sbb[4 * j + 2] : ninf);
            sbb[4 * j + 3] = t >= -7 ? sc[4 * j + 3] : (pf ? sbb[4 * j + 3] : ninf);
          }
        }
        uint32_t pm[16];
        softmax_unit(sbb, true, m0, m1, al0, al1, pm);
        mbar_wait(BAR(B_VB + ef));
        mbar_wait(BAR(B_VB + sd));
        WG_WAIT(1);
        pin(o);
#pragma unroll
        for (int j = 0; j < 8; j++) {
          const int t = t0 - 8 * j;
          const uint32_t k0 = (t >= 0 ? 0xffffu : 0u) | (t >= 1 ? 0xffff0000u : 0u);
          const uint32_t k1 = (t >= -8 ? 0xffffu : 0u) | (t >= -7 ? 0xffff0000u : 0u);
          pd[2 * j] = pm[2 * j] & k0;         p[2 * j] = pm[2 * j] & ~k0;
          pd[2 * j + 1] = pm[2 * j + 1] & k1; p[2 * j + 1] = pm[2 * j + 1] & ~k1;
        }
        rescale(o, al0, al1);
        WG_FENCE();
        pv(o, p, vd + ef * 512);
        pv(o, pd, vd + sd * 512);
        WG_COMMIT();
        WG_WAIT(0);
        pin(o);
        pin(sa);
        {
          const float i0 = 1.0f / (hd ? o[16] : o[0]), i1 = 1.0f / (hd ? o[18] : o[2]);
          uint32_t e[8];
#pragma unroll
          for (int j = 0; j < 4; j++) {
            e[2 * j] = pack2((hd ? o[4 * j] : o[4 * j + 4]) * i0, (hd ? o[4 * j + 1] : o[4 * j + 5]) * i0);
            e[2 * j + 1] = pack2((hd ? o[4 * j + 2] : o[4 * j + 6]) * i1, (hd ? o[4 * j + 3] : o[4 * j + 7]) * i1);
          }
          if (hd && c < 2) { e[0] = 0; e[1] = 0; }
          if (!hd && c >= 2) { e[6] = 0; e[7] = 0; }
          st_pkt(op, e[0], e[1], e[2], epoch);
          st_pkt(op + 128, e[3], e[4], e[5], epoch);
          st_pkt(op + 256, e[6], e[7], 0u, epoch);
        }
        TS(4 + hd);
        op += 384;
        kd = kdn;
        vd += 256;
#pragma unroll
        for (int i = 0; i < 8; i++) qa[i] = qb[i];
      }
      warp_arrive(BAR(B_ATD), lane);
    }

    uint32_t hh[14], ln[14];
    uint32_t key0, key1, k1w, k2w;
    const int piece = 2 * quart + w;
    const int grow = rb * 128 + half * 64 + 16 * v + r;
    {
      float acc[56];
      uint32_t wr[7];
#pragma unroll
      for (int j = 0; j < 7; j++) wr[j] = __ldg((const uint32_t*)P.wr + piece * 28 + 4 * j + c);
      const uint64_t d = mkdesc(sb + (w ? OFF_WV : OFF_WQ), 28672, 1024, 1);
      const uint4* ip = g_o + ((rb * 8 + 4 * w) * 2 + half) * 768 + wt;
      mbar_wait(BAR(B_WOF + w));
#pragma unroll
      for (int hd = 0; hd < 2; hd++) {
        uint4 q[12];
        int t0 = 0;
        while (true) {
          bool ok = true;
#pragma unroll
          for (int i = 0; i < 12; i++) q[i] = ld_pkt(ip + (i / 3) * 1536 + hd * 384 + (i % 3) * 128);
#pragma unroll
          for (int i = 0; i < 12; i++) ok &= (q[i].w == epoch);
          if (__all_sync(~0u, ok)) break;
          spin_guard(t0);
        }
        WG_FENCE();
#pragma unroll
        for (int pp = 0; pp < 4; pp++) {
          const uint64_t dd = d + (7 * pp + 3 * hd) * 64;
          if (hd == 0 && pp == 0) wg112<0>(acc, q[0].x, q[0].y, q[0].z, q[1].x, dd);
          else wg112<1>(acc, q[3 * pp].x, q[3 * pp].y, q[3 * pp].z, q[3 * pp + 1].x, dd);
          wg112<1>(acc, q[3 * pp + 1].y, q[3 * pp + 1].z, q[3 * pp + 2].x, q[3 * pp + 2].y, dd + 128);
        }
        WG_COMMIT();
        TS(6 + hd);
      }
      mbar_wait(BAR(B_ATD));
      mbar_wait(BAR(B_XRF));
      mbar_wait(BAR(B_SW));
      WG_WAIT(0);
      pin(acc);
      const uint32_t ex = sb + OFF_EX + wt * 16;
#pragma unroll
      for (int j = 0; j < 7; j++) {
        if (w) sts128f(ex + 14336 + j * 2048, acc[4 * j], acc[4 * j + 1], acc[4 * j + 2], acc[4 * j + 3]);
        else sts128f(ex + j * 2048, acc[28 + 4 * j], acc[29 + 4 * j], acc[30 + 4 * j], acc[31 + 4 * j]);
      }
      bar_sync(1, 256);
      const uint32_t xr = sb + OFF_XR + (16 * v + r) * 224 + 112 * w + 4 * c;
      float s0 = 0.f, s1 = 0.f, u0 = 0.f, u1 = 0.f, d0 = 0.f, d1 = 0.f;
#pragma unroll
      for (int j = 0; j < 7; j++) {
        const float4 y = lds128f(ex + (w ? 0 : 14336) + j * 2048);
        const float z0 = (w ? acc[28 + 4 * j] : acc[4 * j]) + y.x, z1 = (w ? acc[29 + 4 * j] : acc[4 * j + 1]) + y.y;
        const float z2 = (w ? acc[30 + 4 * j] : acc[4 * j + 2]) + y.z, z3 = (w ? acc[31 + 4 * j] : acc[4 * j + 3]) + y.w;
        hh[2 * j] = hadd2(lds32(xr + 16 * j), pack2(z0, z1));
        hh[2 * j + 1] = hadd2(lds32(xr + 8 * 224 + 16 * j), pack2(z2, z3));
        const float a0 = bf_lo(hh[2 * j]), a1 = bf_hi(hh[2 * j]), b0 = bf_lo(hh[2 * j + 1]), b1 = bf_hi(hh[2 * j + 1]);
        const float w0 = bf_lo(wr[j]), w1 = bf_hi(wr[j]);
        s0 += a0 + a1; u0 = fmaf(a0, a0, fmaf(a1, a1, u0)); d0 = fmaf(a0, w0, fmaf(a1, w1, d0));
        s1 += b0 + b1; u1 = fmaf(b0, b0, fmaf(b1, b1, u1)); d1 = fmaf(b0, w0, fmaf(b1, w1, d1));
      }
#pragma unroll
      for (int o = 1; o < 4; o <<= 1) {
        s0 += __shfl_xor_sync(~0u, s0, o); u0 += __shfl_xor_sync(~0u, u0, o); d0 += __shfl_xor_sync(~0u, d0, o);
        s1 += __shfl_xor_sync(~0u, s1, o); u1 += __shfl_xor_sync(~0u, u1, o); d1 += __shfl_xor_sync(~0u, d1, o);
      }
      uint4* sp = g_st + (rb * 2 + half) * 512 + 16 * v + r;
      if (c < 2)
        st_pkt(sp + piece * 64 + 8 * c, __float_as_uint(c ? s1 : s0), __float_as_uint(c ? u1 : u0), __float_as_uint(c ? d1 : d0), epoch);
      TS(8);
      {
        int t0 = 0;
        while (true) {
          const uint4 a0 = ld_pkt(sp + c * 128), a1 = ld_pkt(sp + c * 128 + 64), b0 = ld_pkt(sp + c * 128 + 8), b1 = ld_pkt(sp + c * 128 + 72);
          const bool ok = a0.w == epoch && a1.w == epoch && b0.w == epoch && b1.w == epoch;
          s0 = __uint_as_float(a0.x) + __uint_as_float(a1.x); u0 = __uint_as_float(a0.y) + __uint_as_float(a1.y);
          d0 = __uint_as_float(a0.z) + __uint_as_float(a1.z);
          s1 = __uint_as_float(b0.x) + __uint_as_float(b1.x); u1 = __uint_as_float(b0.y) + __uint_as_float(b1.y);
          d1 = __uint_as_float(b0.z) + __uint_as_float(b1.z);
          if (__all_sync(~0u, ok)) break;
          spin_guard(t0);
        }
      }
#pragma unroll
      for (int o = 1; o < 4; o <<= 1) {
        s0 += __shfl_xor_sync(~0u, s0, o); u0 += __shfl_xor_sync(~0u, u0, o); d0 += __shfl_xor_sync(~0u, d0, o);
        s1 += __shfl_xor_sync(~0u, s1, o); u1 += __shfl_xor_sync(~0u, u1, o); d1 += __shfl_xor_sync(~0u, d1, o);
      }
      const float mu0 = s0 * (1.f / D_), mu1 = s1 * (1.f / D_);
      const float rs0 = ln_rstd(u0 * (1.f / D_) - mu0 * mu0), rs1 = ln_rstd(u1 * (1.f / D_) - mu1 * mu1);
      const uint32_t mb0 = pack2(mu0, mu0), mb1 = pack2(mu1, mu1);
      const float sw = __uint_as_float(lds32(sb + OFF_MISC + 16));
      const uint32_t rr = pack2((d0 - bf_lo(mb0) * sw) * rs0, (d1 - bf_lo(mb1) * sw) * rs1);
      const uint32_t ro = rr ^ (0x80008000u | (((rr >> 15) & 0x00010001u) * 0x7fffu));
      key0 = (ro << 16) | (0xffffu - grow);
      key1 = (ro & 0xffff0000u) | (0xffffu - (grow + 8));
      k1w = __reduce_max_sync(~0u, max(key0, key1));
      k2w = __reduce_max_sync(~0u, key0 == k1w ? key1 : key1 == k1w ? key0 : max(key0, key1));
      if (w == 0 && quart == v && lane < 2) st_pkt(g_top + ((rb * 2 + half) * 4 + v) * 2 + lane, k1w, k2w, 0u, epoch);
      if (tid == 0) mbar_arrive(BAR(B_E3D));
      TS(9);
#pragma unroll
      for (int j = 0; j < 7; j++) {
        const uint32_t t0 = hsub2(hh[2 * j], mb0), t1 = hsub2(hh[2 * j + 1], mb1);
        ln[2 * j] = pack2(bf_lo(t0) * rs0, bf_hi(t0) * rs0);
        ln[2 * j + 1] = pack2(bf_lo(t1) * rs1, bf_hi(t1) * rs1);
      }
#pragma unroll
      for (int hf = 0; hf < 2; hf++) {
        const uint32_t key = hf ? key1 : key0;
        if (key == k1w || key == k2w) {
          uint4* cp = g_cand + ((grow + 8 * hf) * 8 + piece) * 24 + c;
          st_pkt(cp, ln[hf], ln[2 + hf], ln[4 + hf], epoch);
          st_pkt(cp + 4, ln[6 + hf], ln[8 + hf], ln[10 + hf], epoch);
          st_pkt(cp + 8, ln[12 + hf], 0u, 0u, epoch);
          st_pkt(cp + 12, hh[hf], hh[2 + hf], hh[4 + hf], epoch);
          st_pkt(cp + 16, hh[6 + hf], hh[8 + hf], hh[10 + hf], epoch);
          st_pkt(cp + 20, hh[12 + hf], 0u, 0u, epoch);
        }
      }
#pragma unroll
      for (int j = 0; j < 7; j++) {
        sts32(xr + 16 * j, hadd2(hh[2 * j], ln[2 * j]));
        sts32(xr + 8 * 224 + 16 * j, hadd2(hh[2 * j + 1], ln[2 * j + 1]));
      }
      fence_async();
      bar_sync(1, 256);
    }
    const int srow = rb * 128 + half * 64 + 16 * v + lane;
    const uint32_t sinv = 0xffffu - srow;
    const bool storer = w == 0 && lane < 16;
    const bool cand = sinv == (k1w & 0xffffu) || sinv == (k2w & 0xffffu);
    char* optr = (char*)P.out + srow * 896 + quart * 224;
    const uint32_t osrc = sb + OFF_XR + (16 * v + lane) * 224;
    if (storer && !cand) bulk_s2g(optr, osrc, 224);
    TS(10);

    const bool ffn = bid < 112;
    uint32_t ag[14], au[14], ad[16];
    if (ffn) {
      mbar_wait(BAR(B_FFW));
      const uint32_t wa = sb + OFF_WG + (56 * warp + (lane & 7) + ((lane >> 4) & 1) * 8) * 32 + ((lane >> 3) & 1) * 16;
#pragma unroll
      for (int s = 0; s < 3; s++) {
        ldsm4t(ag[4 * s], ag[4 * s + 1], ag[4 * s + 2], ag[4 * s + 3], wa + s * 512);
        ldsm4t(au[4 * s], au[4 * s + 1], au[4 * s + 2], au[4 * s + 3], wa + 14336 + s * 512);
      }
      const uint32_t wb = sb + OFF_WG + (56 * warp + 48 + (lane & 7)) * 32 + ((lane >> 3) & 1) * 16;
      ldsm2t(ag[12], ag[13], wb);
      ldsm2t(au[12], au[13], wb + 14336);
      const uint32_t wc = sb + OFF_WD + ((lane & 7) + ((lane >> 4) & 1) * 8) * 896 + (56 * warp + ((lane >> 3) & 1) * 8) * 2;
#pragma unroll
      for (int m = 0; m < 4; m++) ldsm4t(ad[4 * m], ad[4 * m + 1], ad[4 * m + 2], ad[4 * m + 3], wc + m * 32);
    }
    mbar_wait(BAR(B_TOP));
    const uint32_t K1 = lds32(sb + OFF_MISC), K2 = lds32(sb + OFF_MISC + 4);
    TS(11);
    const bool fin = bid >= 96;
    const int fj = bid - 96, fr = (tid >> 2) & 7, fe = tid & 3;
    const int fcl = 16 * (fj & 3) + fr + 8 * (fe >> 1);
    const uint32_t fkey = (fe & 1) ? K2 : K1;
    const int frow = 0xffff - (fkey & 0xffffu);
    const bool fval = fin && tid < 32 && fcl < 56;
    if (ffn) {
      uint32_t b[7] = {0u, 0u, 0u, 0u, 0u, 0u, 0u};
      {
        const int row = 0xffff - (((lane & 4) ? K2 : K1) & 0xffffu);
        const uint4* cp = g_cand + (row * 8 + warp) * 24 + c;
        int t0 = 0;
        while (true) {
          bool ok = true;
          if (lane < 8) {
            const uint4 q0 = ld_pkt(cp), q1 = ld_pkt(cp + 4), q2 = ld_pkt(cp + 8);
            ok = q0.w == epoch && q1.w == epoch && q2.w == epoch;
            b[0] = q0.x; b[1] = q0.y; b[2] = q0.z; b[3] = q1.x; b[4] = q1.y; b[5] = q1.z; b[6] = q2.x;
          }
          if (__all_sync(~0u, ok)) break;
          spin_guard(t0);
        }
      }
      float cg[4] = {0.f, 0.f, 0.f, 0.f}, cu[4] = {0.f, 0.f, 0.f, 0.f};
#pragma unroll
      for (int s = 0; s < 3; s++) {
        mma16816(cg, ag[4 * s], ag[4 * s + 1], ag[4 * s + 2], ag[4 * s + 3], b[2 * s], b[2 * s + 1]);
        mma16816(cu, au[4 * s], au[4 * s + 1], au[4 * s + 2], au[4 * s + 3], b[2 * s], b[2 * s + 1]);
      }
      mma1688(cg, ag[12], ag[13], b[6]);
      mma1688(cu, au[12], au[13], b[6]);
      const uint32_t red = sb + OFF_RED;
      if (c == 0) {
        sts64f(red + warp * 256 + r * 8, cg[0], cg[1]);
        sts64f(red + warp * 256 + 64 + r * 8, cg[2], cg[3]);
        sts64f(red + warp * 256 + 128 + r * 8, cu[0], cu[1]);
        sts64f(red + warp * 256 + 192 + r * 8, cu[2], cu[3]);
      }
      bar_sync(1, 256);
      float g = 0.f, u = 0.f;
      const uint32_t ra = red + (lane & 15) * 8 + (lane >> 4) * 4;
#pragma unroll
      for (int i = 0; i < 8; i++) {
        g += __uint_as_float(lds32(ra + i * 256));
        u += __uint_as_float(lds32(ra + i * 256 + 128));
      }
      g = bfr(g);
      const float act = bfr(bfr(g / (1.0f + __expf(-g))) * bfr(u));
      const int sl = (lane & 4) * 4 + 2 * c;
      const float x0 = __shfl_sync(~0u, act, sl), x1 = __shfl_sync(~0u, act, sl + 1);
      const float x2 = __shfl_sync(~0u, act, sl + 8), x3 = __shfl_sync(~0u, act, sl + 9);
      const uint32_t b0 = lane < 8 ? pack2(x0, x1) : 0u, b1 = lane < 8 ? pack2(x2, x3) : 0u;
      uint4* yp = g_y + bid * 256 + warp * 32 + r;
#pragma unroll
      for (int m = 0; m < 4; m++) {
        float y[4] = {0.f, 0.f, 0.f, 0.f};
        mma16816(y, ad[4 * m], ad[4 * m + 1], ad[4 * m + 2], ad[4 * m + 3], b0, b1);
        if (c == 0)
          st_pkt(yp + m * 8, (__float_as_uint(y[0]) & ~1u) | (epoch & 1u), __float_as_uint(y[1]), __float_as_uint(y[2]), __float_as_uint(y[3]));
      }
    }
    TS(12);
    if (storer && cand && sinv != (K1 & 0xffffu) && sinv != (K2 & 0xffffu)) bulk_s2g(optr, osrc, 224);
    if (storer) asm volatile("cp.async.bulk.commit_group;" ::: "memory");
    if (fin) {
      float lnv = 0.f, hv = 0.f;
      int t0 = 0;
      if (fval) {
        const int tile = fcl >> 3;
        const uint4* cp = g_cand + (frow * 8 + (fj >> 2)) * 24 + (tile / 3) * 4 + ((fcl & 7) >> 1);
        while (true) {
          const uint4 q0 = ld_pkt(cp), q1 = ld_pkt(cp + 12);
          const int sl = tile % 3;
          const uint32_t a = sl == 0 ? q0.x : sl == 1 ? q0.y : q0.z, bq = sl == 0 ? q1.x : sl == 1 ? q1.y : q1.z;
          lnv = (fcl & 1) ? bf_hi(a) : bf_lo(a);
          hv = (fcl & 1) ? bf_hi(bq) : bf_lo(bq);
          if (q0.w == epoch && q1.w == epoch) break;
          spin_guard(t0);
        }
      }
      __syncwarp();
      const uint4* yp = g_y + (tid >> 3) * 256 + fj * 8 + (tid & 7);
      float y0, y1, y2, y3;
      while (true) {
        bool ok = true;
        y0 = y1 = y2 = y3 = 0.f;
#pragma unroll
        for (int i = 0; i < 4; i++) {
          if (i < 3 || tid < 128) {
            const uint4 q = ld_pkt(yp + i * 32 * 256);
            ok &= ((q.x ^ epoch) & 1u) == 0;
            y0 += __uint_as_float(q.x); y1 += __uint_as_float(q.y); y2 += __uint_as_float(q.z); y3 += __uint_as_float(q.w);
          }
        }
        if (__all_sync(~0u, ok)) break;
        spin_guard(t0);
      }
#pragma unroll
      for (int o = 8; o < 32; o <<= 1) {
        y0 += __shfl_xor_sync(~0u, y0, o); y1 += __shfl_xor_sync(~0u, y1, o);
        y2 += __shfl_xor_sync(~0u, y2, o); y3 += __shfl_xor_sync(~0u, y3, o);
      }
      const uint32_t red = sb + OFF_RED2;
      if (lane < 8) sts128f(red + warp * 128 + lane * 16, y0, y1, y2, y3);
      bar_sync(1, 256);
      if (fval) {
        float y = 0.f;
#pragma unroll
        for (int i = 0; i < 8; i++) y += __uint_as_float(lds32(red + i * 128 + tid * 4));
        const uint32_t ob = fkey >> 16;
        const float rv = __uint_as_float(((ob & 0x8000u) ? (ob ^ 0x8000u) : (~ob & 0xffffu)) << 16);
        const float sg = bfr(1.0f / (1.0f + __expf(-rv)));
        const float res = hv + bfr(lnv + bfr(bfr(y) * sg));
        P.out[frow * D_ + 56 * (fj >> 2) + fcl] = __float2bfloat16(res);
      }
    }
    if (storer) asm volatile("cp.async.bulk.wait_group 0;" ::: "memory");
    TS(13);
  }
#undef BAR
}

typedef CUresult (*EncodeFn)(CUtensorMap*, CUtensorMapDataType, cuuint32_t, void*, const cuuint64_t*, const cuuint64_t*,
                             const cuuint32_t*, const cuuint32_t*, CUtensorMapInterleave, CUtensorMapSwizzle,
                             CUtensorMapL2promotion, CUtensorMapFloatOOBfill);

void make_map(EncodeFn enc, CUtensorMap* m, const void* p, int cols, int rows, int bc, int br, CUtensorMapSwizzle sw) {
  cuuint64_t gd[2] = {(cuuint64_t)cols, (cuuint64_t)rows};
  cuuint64_t gs[1] = {(cuuint64_t)cols * 2};
  cuuint32_t bx[2] = {(cuuint32_t)bc, (cuuint32_t)br};
  cuuint32_t es[2] = {1, 1};
  enc(m, CU_TENSOR_MAP_DATA_TYPE_BFLOAT16, 2, (void*)p, gd, gs, bx, es, CU_TENSOR_MAP_INTERLEAVE_NONE, sw,
      CU_TENSOR_MAP_L2_PROMOTION_L2_128B, CU_TENSOR_MAP_FLOAT_OOB_FILL_NONE);
}

}

extern "C" void kernel_launch(void* const* d_in, const int* in_sizes, int n_in, void* d_out, int out_size) {
  (void)in_sizes; (void)n_in; (void)out_size;
  static EncodeFn enc = nullptr;
  if (!enc) {
    void* fn = nullptr;
    cudaDriverEntryPointQueryResult qr;
    cudaGetDriverEntryPoint("cuTensorMapEncodeTiled", &fn, cudaEnableDefault, &qr);
    enc = (EncodeFn)fn;
    cudaFuncSetAttribute(fused_kernel, cudaFuncAttributeMaxDynamicSharedMemorySize, SMEM_BYTES);
  }
  const void* x = d_in[0];
  CUtensorMap tx, tw, two, txr, tg, tu;
  make_map(enc, &tx, x, D_, S_, 64, 128, CU_TENSOR_MAP_SWIZZLE_128B);
  make_map(enc, &tw, d_in[1], 3 * D_, D_, 64, 64, CU_TENSOR_MAP_SWIZZLE_128B);
  make_map(enc, &two, d_in[2], D_, D_, 64, 224, CU_TENSOR_MAP_SWIZZLE_128B);
  make_map(enc, &txr, x, D_, S_, 112, 64, CU_TENSOR_MAP_SWIZZLE_NONE);
  make_map(enc, &tg, d_in[5], F_, D_, 16, 224, CU_TENSOR_MAP_SWIZZLE_NONE);
  make_map(enc, &tu, d_in[6], F_, D_, 16, 224, CU_TENSOR_MAP_SWIZZLE_NONE);
  Params p;
  p.wqkv = (const __nv_bfloat16*)d_in[1];
  p.wo = (const __nv_bfloat16*)d_in[2];
  p.wr = (const __nv_bfloat16*)d_in[4];
  p.wg = (const __nv_bfloat16*)d_in[5];
  p.wu = (const __nv_bfloat16*)d_in[6];
  p.wd = (const __nv_bfloat16*)d_in[7];
  p.out = (__nv_bfloat16*)d_out;
  fused_kernel<<<NCTA, NTHR, SMEM_BYTES>>>(tx, tw, two, txr, tg, tu, p);
}
```

```cpp
#include <cuda_runtime.h>
#include <cuda_bf16.h>
#include <cuda.h>
#include <stdint.h>

namespace {

constexpr int D_ = 448, F_ = 1792, S_ = 2048;
constexpr int NCTA = 128, NTHR = 384;
#define FORCE_FALLBACK 0
#define XPF 0
#define MAPV 0
#define SERCEN 1
#define FFAT 1
#define OUTAT 0
#define OPRE 1
#define WKD 0
#define WVD 1
#define WPF 0
#define FDELAY 0

constexpr uint32_t OFF_WK = 0;
constexpr uint32_t OFF_X = 57344;
constexpr uint32_t OFF_KA = 57344;
constexpr uint32_t OFF_XR = 100352;
constexpr uint32_t OFF_WQ = 114688;
constexpr uint32_t OFF_WV = 172032;
constexpr uint32_t OFF_BAR = 229376;
constexpr uint32_t OFF_MISC = OFF_BAR + 512;
constexpr uint32_t SMEM_BYTES = 232448;
constexpr uint32_t OFF_VA = 0;
constexpr uint32_t OFF_EX = 0;
constexpr uint32_t OFF_RED = 28672;
constexpr uint32_t OFF_RED2 = 32768;
constexpr uint32_t OFF_WG = OFF_KA, OFF_WU = OFF_KA + 14336, OFF_WD = OFF_KA + 28672;

enum { B_WKF = 0  , B_WVF = 2, B_WQF = 3, B_WOF = 4  , B_FFW = 6, B_TOP = 7, B_E3D = 8, B_SW = 9, B_XRF = 10,
       B_FB = 11  , B_KB = 15  , B_VB = 21  ,
       B_CEN = 27,
       B_XE = 28, B_KPD = 29, B_QPD = 30, B_ATD = 31, B_OGD = 32, B_KEY = 33,
       B_XT = 36   };

struct Scratch {
  uint4 kv[NCTA * 2 * 2 * 512];
  uint4 o[NCTA * 2 * 2 * 2 * 128];
  uint4 st[32 * 4 * 64];
  uint4 flag[NCTA * 8];
  uint4 top[32 * 2];
  uint4 cand[S_ * 8 * 6 * 4];
  uint4 y[112 * 256];
  uint32_t epoch;
};
__device__ Scratch g_scratch;
#define TS(i)
#define TSV(i, val)
#define TSX(i)
#define TS_DUMP()

__device__ __forceinline__ void spin_guard(int& n) {
  if (++n > (1 << 21)) __trap();
}
__device__ __forceinline__ void mbar_init(uint32_t bar, uint32_t cnt) {
  asm volatile("mbarrier.init.shared::cta.b64 [%0], %1;" ::"r"(bar), "r"(cnt) : "memory");
}
__device__ __forceinline__ void mbar_expect(uint32_t bar, uint32_t bytes) {
  asm volatile("mbarrier.arrive.expect_tx.shared::cta.b64 _, [%0], %1;" ::"r"(bar), "r"(bytes) : "memory");
}
__device__ __forceinline__ void mbar_arrive(uint32_t bar) {
  asm volatile("mbarrier.arrive.shared::cta.b64 _, [%0];" ::"r"(bar) : "memory");
}
__device__ __forceinline__ void mbar_wait(uint32_t bar) {
  asm volatile("{\n.reg .pred p;\n.reg .u32 n;\nmov.u32 n, 0;\nMW_LOOP:\n"
               "mbarrier.try_wait.parity.shared::cta.b64 p, [%0], 0;\n@p bra MW_DONE;\n"
               "add.u32 n, n, 1;\nsetp.lt.u32 p, n, 4194304;\n@p bra MW_LOOP;\ntrap;\nMW_DONE:\n}" ::"r"(bar) : "memory");
}
__device__ __forceinline__ void mbar_wait_par(uint32_t bar, uint32_t par) {
  asm volatile("{\n.reg .pred p;\n.reg .u32 n;\nmov.u32 n, 0;\nMW_LOOP:\n"
               "mbarrier.try_wait.parity.shared::cta.b64 p, [%0], %1;\n@p bra MW_DONE;\n"
               "add.u32 n, n, 1;\nsetp.lt.u32 p, n, 4194304;\n@p bra MW_LOOP;\ntrap;\nMW_DONE:\n}" ::"r"(bar), "r"(par) : "memory");
}
__device__ __forceinline__ uint32_t mbar_test(uint32_t bar) {
  uint32_t ok;
  asm volatile("{\n.reg .pred p;\nmbarrier.test_wait.parity.shared::cta.b64 p, [%1], 0;\nselp.u32 %0, 1, 0, p;\n}" : "=r"(ok) : "r"(bar) : "memory");
  return ok;
}
__device__ __forceinline__ void warp_arrive(uint32_t bar, int lane) {
  __syncwarp();
  if (lane == 0) mbar_arrive(bar);
}
__device__ __forceinline__ void fence_async() { asm volatile("fence.proxy.async.shared::cta;" ::: "memory"); }
__device__ __forceinline__ void tma2d(uint32_t dst, const CUtensorMap* m, int c0, int c1, uint32_t bar) {
  asm volatile("cp.async.bulk.tensor.2d.shared::cluster.global.mbarrier::complete_tx::bytes [%0], [%1, {%3, %4}], [%2];"
               ::"r"(dst), "l"(m), "r"(bar), "r"(c0), "r"(c1) : "memory");
}
__device__ __forceinline__ void bulk_g2s(uint32_t dst, const void* src, uint32_t bytes, uint32_t bar) {
  asm volatile("cp.async.bulk.shared::cluster.global.mbarrier::complete_tx::bytes [%0], [%1], %2, [%3];"
               ::"r"(dst), "l"(src), "r"(bytes), "r"(bar) : "memory");
}
__device__ __forceinline__ void bulk_s2g(void* dst, uint32_t src, uint32_t bytes) {
  asm volatile("cp.async.bulk.global.shared::cta.bulk_group [%0], [%1], %2;" ::"l"(dst), "r"(src), "r"(bytes) : "memory");
}
__device__ __forceinline__ void l2_prefetch(const void* p, uint32_t bytes) {
  asm volatile("cp.async.bulk.prefetch.L2.global [%0], %1;" ::"l"(p), "r"(bytes) : "memory");
}
__device__ __forceinline__ void st_pkt(uint4* p, uint32_t a, uint32_t b, uint32_t c, uint32_t d) {
  asm volatile("st.relaxed.gpu.global.v4.u32 [%0], {%1, %2, %3, %4};" ::"l"(p), "r"(a), "r"(b), "r"(c), "r"(d) : "memory");
}
__device__ __forceinline__ uint4 ld_pkt(const uint4* p) {
  uint4 v;
  asm volatile("ld.relaxed.gpu.global.v4.u32 {%0, %1, %2, %3}, [%4];" : "=r"(v.x), "=r"(v.y), "=r"(v.z), "=r"(v.w) : "l"(p) : "memory");
  return v;
}
__device__ __forceinline__ void ldsm4(uint32_t& r0, uint32_t& r1, uint32_t& r2, uint32_t& r3, uint32_t a) {
  asm volatile("ldmatrix.sync.aligned.m8n8.x4.shared.b16 {%0,%1,%2,%3}, [%4];"
               : "=r"(r0), "=r"(r1), "=r"(r2), "=r"(r3) : "r"(a) : "memory");
}
__device__ __forceinline__ void ldsm4t(uint32_t& r0, uint32_t& r1, uint32_t& r2, uint32_t& r3, uint32_t a) {
  asm volatile("ldmatrix.sync.aligned.m8n8.x4.trans.shared.b16 {%0,%1,%2,%3}, [%4];"
               : "=r"(r0), "=r"(r1), "=r"(r2), "=r"(r3) : "r"(a) : "memory");
}
__device__ __forceinline__ void ldsm2t(uint32_t& r0, uint32_t& r1, uint32_t a) {
  asm volatile("ldmatrix.sync.aligned.m8n8.x2.trans.shared.b16 {%0,%1}, [%2];" : "=r"(r0), "=r"(r1) : "r"(a) : "memory");
}
__device__ __forceinline__ void stsm4(uint32_t a, uint32_t r0, uint32_t r1, uint32_t r2, uint32_t r3) {
  asm volatile("stmatrix.sync.aligned.m8n8.x4.shared.b16 [%0], {%1,%2,%3,%4};" ::"r"(a), "r"(r0), "r"(r1), "r"(r2), "r"(r3) : "memory");
}
__device__ __forceinline__ void stsm2(uint32_t a, uint32_t r0, uint32_t r1) {
  asm volatile("stmatrix.sync.aligned.m8n8.x2.shared.b16 [%0], {%1,%2};" ::"r"(a), "r"(r0), "r"(r1) : "memory");
}
__device__ __forceinline__ void mma16816(float (&c)[4], uint32_t a0, uint32_t a1, uint32_t a2, uint32_t a3, uint32_t b0, uint32_t b1) {
  asm volatile("mma.sync.aligned.m16n8k16.row.col.f32.bf16.bf16.f32 {%0,%1,%2,%3}, {%4,%5,%6,%7}, {%8,%9}, {%0,%1,%2,%3};"
               : "+f"(c[0]), "+f"(c[1]), "+f"(c[2]), "+f"(c[3]) : "r"(a0), "r"(a1), "r"(a2), "r"(a3), "r"(b0), "r"(b1));
}
__device__ __forceinline__ void mma1688(float (&c)[4], uint32_t a0, uint32_t a1, uint32_t b0) {
  asm volatile("mma.sync.aligned.m16n8k8.row.col.f32.bf16.bf16.f32 {%0,%1,%2,%3}, {%4,%5}, {%6}, {%0,%1,%2,%3};"
               : "+f"(c[0]), "+f"(c[1]), "+f"(c[2]), "+f"(c[3]) : "r"(a0), "r"(a1), "r"(b0));
}
__device__ __forceinline__ uint32_t pack2(float lo, float hi) {
  uint32_t r;
  asm("cvt.rn.bf16x2.f32 %0, %1, %2;" : "=r"(r) : "f"(hi), "f"(lo));
  return r;
}
__device__ __forceinline__ float bf_lo(uint32_t u) { return __uint_as_float(u << 16); }
__device__ __forceinline__ float bf_hi(uint32_t u) { return __uint_as_float(u & 0xffff0000u); }
__device__ __forceinline__ float bfr(float x) { return bf_lo(pack2(x, 0.f)); }
__device__ __forceinline__ uint32_t hsub2(uint32_t a, uint32_t b) {
  uint32_t r;
  asm("sub.rn.bf16x2 %0, %1, %2;" : "=r"(r) : "r"(a), "r"(b));
  return r;
}
__device__ __forceinline__ uint32_t hadd2(uint32_t a, uint32_t b) {
  uint32_t r;
  asm("add.rn.bf16x2 %0, %1, %2;" : "=r"(r) : "r"(a), "r"(b));
  return r;
}
__device__ __forceinline__ uint32_t hfma2(uint32_t a, uint32_t b, uint32_t c) {
  uint32_t r;
  asm("fma.rn.bf16x2 %0, %1, %2, %3;" : "=r"(r) : "r"(a), "r"(b), "r"(c));
  return r;
}
__device__ __forceinline__ uint32_t hmul2(uint32_t a, uint32_t b) {
  uint32_t r;
  asm("mul.rn.bf16x2 %0, %1, %2;" : "=r"(r) : "r"(a), "r"(b));
  return r;
}
__device__ __forceinline__ float ex2(float x) {
  float r;
  asm("ex2.approx.ftz.f32 %0, %1;" : "=f"(r) : "f"(x));
  return r;
}
__device__ __forceinline__ uint32_t lds32(uint32_t a) {
  uint32_t v;
  asm volatile("ld.shared.u32 %0, [%1];" : "=r"(v) : "r"(a) : "memory");
  return v;
}
__device__ __forceinline__ void sts32(uint32_t a, uint32_t v) { asm volatile("st.shared.u32 [%0], %1;" ::"r"(a), "r"(v) : "memory"); }
__device__ __forceinline__ void sts64f(uint32_t a, float x, float y) {
  asm volatile("st.shared.v2.f32 [%0], {%1,%2};" ::"r"(a), "f"(x), "f"(y) : "memory");
}
__device__ __forceinline__ void sts128f(uint32_t a, float x, float y, float z, float w) {
  asm volatile("st.shared.v4.f32 [%0], {%1,%2,%3,%4};" ::"r"(a), "f"(x), "f"(y), "f"(z), "f"(w) : "memory");
}
__device__ __forceinline__ float4 lds128f(uint32_t a) {
  float4 v;
  asm volatile("ld.shared.v4.f32 {%0,%1,%2,%3}, [%4];" : "=f"(v.x), "=f"(v.y), "=f"(v.z), "=f"(v.w) : "r"(a) : "memory");
  return v;
}
__device__ __forceinline__ uint4 lds128(uint32_t a) {
  uint4 v;
  asm volatile("ld.shared.v4.u32 {%0,%1,%2,%3}, [%4];" : "=r"(v.x), "=r"(v.y), "=r"(v.z), "=r"(v.w) : "r"(a) : "memory");
  return v;
}
__device__ __forceinline__ void sts128(uint32_t a, uint4 v) {
  asm volatile("st.shared.v4.u32 [%0], {%1,%2,%3,%4};" ::"r"(a), "r"(v.x), "r"(v.y), "r"(v.z), "r"(v.w) : "memory");
}
__device__ __forceinline__ void bar_sync(int id, int n) { asm volatile("bar.sync %0, %1;" ::"r"(id), "r"(n) : "memory"); }
__device__ __forceinline__ bool bar_or(int id, int n, bool v) {
  uint32_t r;
  asm volatile("{\n.reg .pred p, q;\nsetp.ne.u32 p, %3, 0;\nbar.red.or.pred q, %1, %2, p;\nselp.u32 %0, 1, 0, q;\n}"
               : "=r"(r) : "r"(id), "r"(n), "r"((uint32_t)v) : "memory");
  return r;
}
__device__ __forceinline__ void bar_arrive(int id, int n) { asm volatile("bar.arrive %0, %1;" ::"r"(id), "r"(n) : "memory"); }
__device__ __forceinline__ uint32_t dlo(uint32_t addr, uint32_t lbo) { return ((addr & 0x3FFFF) >> 4) | ((lbo >> 4) << 16); }
constexpr uint32_t HI_SW128 = 0x40000040u;
constexpr uint32_t HI_K = 8u;
constexpr uint32_t HI_V = 64u;
#define WG_FENCE() asm volatile("wgmma.fence.sync.aligned;" ::: "memory")
#define WG_COMMIT() asm volatile("wgmma.commit_group.sync.aligned;" ::: "memory")
#define WG_WAIT(n) asm volatile("wgmma.wait_group.sync.aligned " #n ";" ::: "memory")
template <int N> __device__ __forceinline__ void pin(float (&d)[N]) {
#pragma unroll
  for (int i = 0; i < N; i++) asm volatile("" : "+f"(d[i])::"memory");
}

#define R4(d, i) "+f"(d[i]), "+f"(d[i + 1]), "+f"(d[i + 2]), "+f"(d[i + 3])
template <int ACC> __device__ __forceinline__ void wg32(float (&d)[16], uint32_t a0, uint32_t a1, uint32_t a2, uint32_t a3, uint32_t b) {
  asm volatile("{\n.reg .b64 dsc;\nmov.b64 dsc, {%20, %21};\nwgmma.mma_async.sync.aligned.m64n32k16.f32.bf16.bf16 "
               "{%0,%1,%2,%3,%4,%5,%6,%7,%8,%9,%10,%11,%12,%13,%14,%15}, {%16,%17,%18,%19}, dsc, %22, 1, 1, 1;\n}"
               : R4(d, 0), R4(d, 4), R4(d, 8), R4(d, 12) : "r"(a0), "r"(a1), "r"(a2), "r"(a3), "r"(b), "n"(HI_V), "n"(ACC));
}
template <int ACC> __device__ __forceinline__ void wg56(float (&d)[28], uint32_t a0, uint32_t a1, uint32_t a2, uint32_t a3, uint32_t b) {
  asm volatile("{\n.reg .b64 dsc;\nmov.b64 dsc, {%32, %34};\nwgmma.mma_async.sync.aligned.m64n56k16.f32.bf16.bf16 "
               "{%0,%1,%2,%3,%4,%5,%6,%7,%8,%9,%10,%11,%12,%13,%14,%15,%16,%17,%18,%19,%20,%21,%22,%23,%24,%25,%26,%27}, "
               "{%28,%29,%30,%31}, dsc, %33, 1, 1, 1;\n}"
               : R4(d, 0), R4(d, 4), R4(d, 8), R4(d, 12), R4(d, 16), R4(d, 20), R4(d, 24)
               : "r"(a0), "r"(a1), "r"(a2), "r"(a3), "r"(b), "n"(ACC), "n"(HI_SW128));
}
template <int ACC> __device__ __forceinline__ void wg64(float (&d)[32], uint32_t a0, uint32_t a1, uint32_t a2, uint32_t a3, uint32_t b) {
  asm volatile("{\n.reg .b64 dsc;\nmov.b64 dsc, {%36, %38};\nwgmma.mma_async.sync.aligned.m64n64k16.f32.bf16.bf16 "
               "{%0,%1,%2,%3,%4,%5,%6,%7,%8,%9,%10,%11,%12,%13,%14,%15,%16,%17,%18,%19,%20,%21,%22,%23,%24,%25,%26,%27,%28,%29,%30,%31}, "
               "{%32,%33,%34,%35}, dsc, %37, 1, 1, 0;\n}"
               : R4(d, 0), R4(d, 4), R4(d, 8), R4(d, 12), R4(d, 16), R4(d, 20), R4(d, 24), R4(d, 28)
               : "r"(a0), "r"(a1), "r"(a2), "r"(a3), "r"(b), "n"(ACC), "n"(HI_K));
}
template <int ACC> __device__ __forceinline__ void wg112(float (&d)[56], uint32_t a0, uint32_t a1, uint32_t a2, uint32_t a3, uint32_t b) {
  asm volatile("{\n.reg .b64 dsc;\nmov.b64 dsc, {%60, %62};\nwgmma.mma_async.sync.aligned.m64n112k16.f32.bf16.bf16 "
               "{%0,%1,%2,%3,%4,%5,%6,%7,%8,%9,%10,%11,%12,%13,%14,%15,%16,%17,%18,%19,%20,%21,%22,%23,%24,%25,%26,%27,"
               "%28,%29,%30,%31,%32,%33,%34,%35,%36,%37,%38,%39,%40,%41,%42,%43,%44,%45,%46,%47,%48,%49,%50,%51,%52,%53,%54,%55}, "
               "{%56,%57,%58,%59}, dsc, %61, 1, 1, 1;\n}"
               : R4(d, 0), R4(d, 4), R4(d, 8), R4(d, 12), R4(d, 16), R4(d, 20), R4(d, 24), R4(d, 28), R4(d, 32), R4(d, 36),
                 R4(d, 40), R4(d, 44), R4(d, 48), R4(d, 52)
               : "r"(a0), "r"(a1), "r"(a2), "r"(a3), "r"(b), "n"(ACC), "n"(HI_SW128));
}

__device__ __forceinline__ float ln_rstd(float var) {
  float s = bfr(sqrtf(bfr(bfr(fmaxf(var, 0.f)) + 1e-5f)));
  return 1.0f / s;
}
template <int ISV>
__device__ __forceinline__ void kv_epilogue(const float (&acc)[28], float rs0, float rs1, uint32_t img, uint32_t bar, uint32_t par, int v, int lane) {
  uint32_t e[14];
#pragma unroll
  for (int j = 0; j < 7; j++) {
    e[2 * j] = pack2(acc[4 * j] * rs0, acc[4 * j + 1] * rs0);
    e[2 * j + 1] = pack2(acc[4 * j + 2] * rs1, acc[4 * j + 3] * rs1);
  }
  const uint32_t keep = (lane & 3) ? ~0u : ~1u, tag = (lane & 3) ? 0u : par, one = 0x3f803f80u | tag;
#pragma unroll
  for (int j = 0; j < 14; j++) e[j] = (e[j] & keep) | tag;
  const uint32_t a = img + (lane >> 4) * 1024 + (16 * v + (lane & 15)) * 16;
  stsm4(a, e[0], e[1], e[2], e[3]);
  if (ISV) {
    const bool hi = lane & 2;
    stsm4(a + 2048, e[4], e[5], hi ? one : e[6], hi ? one : e[7]);
    stsm4(a + 4096, hi ? e[6] : one, hi ? e[7] : one, e[8], e[9]);
    stsm4(a + 6144, e[10], e[11], e[12], e[13]);
  } else {
    stsm4(a + 2048, e[4], e[5], e[6], e[7]);
    stsm4(a + 4096, e[8], e[9], e[10], e[11]);
    stsm2(a + 6144, e[12], e[13]);
  }
  fence_async();
  warp_arrive(bar, lane);
}

constexpr float SC = 0.18898223650461361f * 1.4426950408889634f;

template <int N> __device__ __forceinline__ void pinu(uint32_t (&d)[N]) {
#pragma unroll
  for (int i = 0; i < N; i++) asm volatile("" : "+r"(d[i])::"memory");
}
__device__ __forceinline__ void exp_pack(const float (&s)[32], uint32_t (&p)[16]) {
#pragma unroll
  for (int i = 0; i < 16; i++) p[i] = pack2(ex2(s[2 * i]), ex2(s[2 * i + 1]));
}
__device__ __forceinline__ void qk(float (&s)[32], const uint32_t (&q)[8], uint32_t kd) {
  wg64<0>(s, q[0], q[1], q[2], q[3], kd);
  wg64<1>(s, q[4], q[5], q[6], q[7], kd + 128);
}
template <int ACC> __device__ __forceinline__ void pv(float (&o)[16], const uint32_t (&p)[16], uint32_t vd) {
  wg32<ACC>(o, p[0], p[1], p[2], p[3], vd);
#pragma unroll
  for (int k = 1; k < 4; k++) wg32<1>(o, p[4 * k], p[4 * k + 1], p[4 * k + 2], p[4 * k + 3], vd + 16 * k);
}
template <int CHECK> __device__ __forceinline__ bool o_epilogue(const float (&o)[16], int hd, uint4* op, uint32_t par, int c, int barid) {
  const bool pad = hd ? c < 2 : c >= 2;
  const float z0 = hd ? o[1] : o[12], z1 = hd ? o[3] : o[14];
  const float y0 = __shfl_xor_sync(~0u, z0, 2), y1 = __shfl_xor_sync(~0u, z1, 2);
  const float l0 = pad ? z0 : y0, l1 = pad ? z1 : y1;
  const float i0 = __fdividef(1.0f, l0), i1 = __fdividef(1.0f, l1);
  uint32_t e[8];
#pragma unroll
  for (int j = 0; j < 4; j++) {
    e[2 * j] = pack2(o[4 * j] * i0, o[4 * j + 1] * i0);
    e[2 * j + 1] = pack2(o[4 * j + 2] * i1, o[4 * j + 3] * i1);
  }
  if (pad && hd) { e[0] = 0; e[1] = 0; }
  if (pad && !hd) { e[6] = 0; e[7] = 0; }
  if (CHECK) {
    const float LO = 9.094947e-13f, HI = 1.0995116e12f;
    if (bar_or(barid, 128, FORCE_FALLBACK || !(l0 >= LO && l0 <= HI && l1 >= LO && l1 <= HI))) return true;
  }
  st_pkt(op, (e[0] & ~1u) | par, e[1], e[2], e[3]);
  st_pkt(op + 128, (e[4] & ~1u) | par, e[5], e[6], e[7]);
  return false;
}

struct Params {
  const __nv_bfloat16* x; const __nv_bfloat16* wqkv; const __nv_bfloat16* wr;
  const __nv_bfloat16* wg; const __nv_bfloat16* wu; const __nv_bfloat16* wd;
  __nv_bfloat16* out;
  Scratch* sc;
  uint32_t zero;
};

__global__ void __launch_bounds__(NTHR, 1)
fused_kernel(const __grid_constant__ CUtensorMap tm_x, const __grid_constant__ CUtensorMap tm_w, const __grid_constant__ CUtensorMap tm_wo,
             const __grid_constant__ CUtensorMap tm_xr,
             const __grid_constant__ CUtensorMap tm_g, const __grid_constant__ CUtensorMap tm_u, const Params P) {
  extern __shared__ __align__(1024) unsigned char smem_raw[];
  const uint32_t sb = (uint32_t)__cvta_generic_to_shared(smem_raw);
  const uint32_t bars = sb + OFF_BAR;
#define BAR(i) (bars + 8 * (i))
  const int tid = threadIdx.x, warp = __shfl_sync(~0u, tid >> 5, 0), lane = tid & 31;
  const int bid = blockIdx.x;
  const int rb = (bid >> 5) * 4 + ((bid >> 2) & 3), hg = ((bid >> 4) & 1) * 4 + (bid & 3);
  const int half = hg >> 2, quart = hg & 3;

  if (tid == 0) asm volatile("prefetch.tensormap [%0];" ::"l"(&tm_x) : "memory");
  if (tid == 32) asm volatile("prefetch.tensormap [%0];" ::"l"(&tm_w) : "memory");
  if (XPF && tid == 64) l2_prefetch((const char*)P.x + (rb * 128 + hg * 16) * 896, 14336);
  if (WPF == 1 && tid == 96) l2_prefetch((const char*)P.wqkv + bid * 9408, 9408);
  if (WPF == 2 && tid >= 96 && tid < 100 && bid < 112) l2_prefetch((const char*)P.wqkv + (bid * 4 + tid - 96) * 2688 + 896, 896);
  const int wcol = ((hg * 112) & ~31) >> 1;
  if (warp < 8) {
    if (lane == 0) {
#pragma unroll
      for (int k = 0; k < 5; k++) {
        const int i = k * 8 + warp;
        if (i <= B_KEY) mbar_init(BAR(i), i >= B_XE ? 8 : (i >= B_VB + 4 || i == B_KB + 4 || i == B_KB + 5) ? 4 : 1);
      }
      asm volatile("fence.mbarrier_init.release.cluster;" ::: "memory");
    }
    __syncwarp();
    bar_arrive(0, NTHR);
    asm volatile("setmaxnreg.inc.sync.aligned.u32 224;");
    uint32_t epoch;
    asm volatile("ld.relaxed.gpu.global.u32 %0, [%1];" : "=r"(epoch) : "l"(&P.sc->epoch) : "memory");
    const int w = warp >> 2, v = warp & 3, r = lane >> 2, c = lane & 3, wt = tid & 127;
    uint32_t qa[8], qb[8], dm[9], k0, k1, k2, kf, kg, v0, v1, v2, vf, vg, b0, b1, b2, bf, bg;
    const int lo = 4 - 2 * rb;
    const int s0 = 3 + w, s1 = 1 + 2 * w, s2 = 2, sf = w, sd = w + 4;
    const bool p0 = s0 >= lo, p1 = s1 >= lo, p2 = s2 >= lo, pf = sf >= lo;
    const uint32_t kdb = dlo(sb + OFF_KA, 1024), vdb = dlo(sb + OFF_VA, 128);
    const int t0 = 16 * v + r - 2 * c;
    {
      {
        const int e0 = p0 ? s0 : 4, e1 = p1 ? s1 : 4, e2 = p2 ? s2 : 4, ef = pf ? sf : 4;
#define UNI(x) __shfl_sync(~0u, (uint32_t)(x), 0)
        k0 = UNI(kdb + e0 * 448); k1 = UNI(kdb + e1 * 448); k2 = UNI(kdb + e2 * 448); kf = UNI(kdb + ef * 448); kg = UNI(kdb + sd * 448);
        v0 = UNI(vdb + e0 * 512); v1 = UNI(vdb + e1 * 512); v2 = UNI(vdb + e2 * 512); vf = UNI(vdb + ef * 512); vg = UNI(vdb + sd * 512);
        b0 = UNI(BAR(e0)); b1 = UNI(BAR(e1)); b2 = UNI(BAR(e2)); bf = UNI(BAR(ef)); bg = UNI(BAR(sd));
#pragma unroll
        for (int j = 0; j < 9; j++) asm volatile("shl.b32 %0, %1, %2;" : "=r"(dm[j]) : "r"(0xffffffffu), "r"(max(0, 16 * (t0 + 9 - 8 * j))));
        if (c == 0) {
          st_pkt(P.sc->st + (rb * 2 + half) * 256 + quart * 64 + 16 * v + r + 8 * w, 0u, 0u, 0u, 0u);
          if (bid < 112) {
#pragma unroll
            for (int m = 0; m < 4; m++) st_pkt(P.sc->y + bid * 256 + warp * 32 + r + 8 * m, epoch & 1u, 0u, 0u, 0u);
          }
        }
        if (quart == 0 && tid < 2) st_pkt(P.sc->top + (rb * 2 + half) * 2 + tid, 0u, 0u, 0u, 0u);
      }
      uint32_t a[112], mb0, mb1;
      float mu0, mu1, rs0, rs1, q0, q1;
      const uint32_t xa = sb + OFF_X + w * 8192 + (16 * v + (lane & 15)) * 128;
      {
        float su[2][4] = {};
        bar_sync(7, NTHR);
#pragma unroll
        for (int kc = 0; kc < 7; kc++) {
          if (kc == 0 || (kc & 1)) { mbar_wait(BAR(B_XT + (kc + 1) / 2)); TS(15 + (kc + 1) / 2); }
#pragma unroll
          for (int s = 0; s < 4; s++) {
            const int i = 16 * kc + 4 * s;
            ldsm4(a[i], a[i + 1], a[i + 2], a[i + 3], xa + kc * 16384 + (((2 * s + (lane >> 4)) ^ (lane & 7)) << 4));
          }
#pragma unroll
          for (int s = 0; s < 4; s++) {
            const int i = 16 * kc + 4 * s;
            mma16816(su[s & 1], a[i], a[i + 1], a[i + 2], a[i + 3], 0x3f803f80u, 0x3f803f80u);
          }
        }
        warp_arrive(BAR(B_XE), lane);
        TS(0);
        if (SERCEN && w == 0) mbar_wait(BAR(B_CEN));
        mu0 = (su[0][0] + su[1][0]) * (1.f / D_); mu1 = (su[0][2] + su[1][2]) * (1.f / D_);
        mb0 = pack2(mu0, mu0); mb1 = pack2(mu1, mu1);
        q0 = 0.f; q1 = 0.f;
#pragma unroll
        for (int i = 0; i < 112; i++) a[i] = hsub2(a[i], (i & 1) ? mb1 : mb0);
#pragma unroll
        for (int g = 0; g < 16; g++) {
          const int b = 14 * (g >> 1) + (g & 1);
          uint32_t z = hmul2(a[b], a[b]);
#pragma unroll
          for (int i = 1; i < 7; i++) z = hfma2(a[b + 2 * i], a[b + 2 * i], z);
          if (g & 1) q1 += bf_lo(z) + bf_hi(z); else q0 += bf_lo(z) + bf_hi(z);
        }
        pinu(a);
        asm volatile("" : "+f"(q0), "+f"(q1)::"memory");
        if (SERCEN && w == 1) { if (lane == 0) mbar_arrive(BAR(B_CEN) + (__float_as_uint(q0 + q1) & P.zero)); }
      }
      epoch += 1;

      const uint32_t wofs = (hg & 1) * 16;
      float acc[28];
      {
        TS(19);
        if (w == 0) bar_sync(1, 256);
        const uint32_t d = dlo(sb + OFF_WK + wofs, 16);
#pragma unroll
        for (int kc = 0; kc < 2; kc++) {
          mbar_wait(BAR(B_WKF + kc));
          WG_FENCE();
#pragma unroll
          for (int s = 0; s < 14; s++) {
            const int k = 14 * kc + s;
            if (k == 0) wg56<0>(acc, a[0], a[1], a[2], a[3], d);
            else wg56<1>(acc, a[4 * k], a[4 * k + 1], a[4 * k + 2], a[4 * k + 3], d + 128 * k);
          }
        }
        WG_COMMIT();
        bar_arrive(2 - w, 256);
#pragma unroll
        for (int o = 1; o < 4; o <<= 1) { q0 += __shfl_xor_sync(~0u, q0, o); q1 += __shfl_xor_sync(~0u, q1, o); }
        const float dm0 = mu0 - bf_lo(mb0), dm1 = mu1 - bf_lo(mb1);
        rs0 = ln_rstd(q0 * (1.f / D_) - dm0 * dm0);
        rs1 = ln_rstd(q1 * (1.f / D_) - dm1 * dm1);
        WG_WAIT(0);
        pin(acc);
        TS(1);
        warp_arrive(BAR(B_KPD), lane);
        TS(20);
        mbar_wait(BAR(B_XE));
        kv_epilogue<0>(acc, rs0, rs1, sb + OFF_KA + (4 + w) * 7168, BAR(B_KB + 4 + w), epoch & 1, v, lane);
      }
      {
        const uint32_t d = dlo(sb + OFF_WV + wofs, 16);
        TS(21);
        mbar_wait(BAR(B_WVF));
        bar_sync(1 + w, 256);
        WG_FENCE();
#pragma unroll
        for (int k = 0; k < 28; k++) {
          if (k == 0) wg56<0>(acc, a[0], a[1], a[2], a[3], d);
          else wg56<1>(acc, a[4 * k], a[4 * k + 1], a[4 * k + 2], a[4 * k + 3], d + 128 * k);
        }
        WG_COMMIT();
        bar_arrive(2 - w, 256);
        WG_WAIT(0);
        pin(acc);
        TS(2);
        mbar_wait(BAR(B_KPD));
        kv_epilogue<1>(acc, rs0, rs1, sb + OFF_VA + (4 + w) * 8192, BAR(B_VB + 4 + w), epoch & 1, v, lane);
      }
      {
        const uint32_t d = dlo(sb + OFF_WQ + wofs, 16);
        mbar_wait(BAR(B_WQF));
        TS(23);
        bar_sync(1 + w, 256);
        WG_FENCE();
#pragma unroll
        for (int k = 0; k < 28; k++) {
          if (k == 0) wg56<0>(acc, a[0], a[1], a[2], a[3], d);
          else wg56<1>(acc, a[4 * k], a[4 * k + 1], a[4 * k + 2], a[4 * k + 3], d + 128 * k);
        }
        WG_COMMIT();
        if (w == 1) bar_arrive(1, 256);
        WG_WAIT(0);
        pin(acc);
        TS(3);
        warp_arrive(BAR(B_QPD), lane);
        uint32_t e[14];
        const float rq0 = rs0 * SC, rq1 = rs1 * SC;
#pragma unroll
        for (int j = 0; j < 7; j++) {
          e[2 * j] = pack2(acc[4 * j] * rq0, acc[4 * j + 1] * rq0);
          e[2 * j + 1] = pack2(acc[4 * j + 2] * rq1, acc[4 * j + 3] * rq1);
        }
#pragma unroll
        for (int i = 0; i < 6; i++) { qa[i] = e[i]; qb[2 + i] = e[8 + i]; }
        qa[6] = c < 2 ? e[6] : 0u; qa[7] = c < 2 ? e[7] : 0u;
        qb[0] = c < 2 ? 0u : e[6]; qb[1] = c < 2 ? 0u : e[7];
      }
    }

    const uint4* ip = P.sc->o + ((rb * 8 + 4 * w) * 2 + half) * 512 + wt;
    uint4 oq[8];
    {
      uint4* op = P.sc->o + ((rb * 8 + hg) * 2 + w) * 512 + wt;
#define BB(k) do { if (P.zero & (1u << (k))) mbar_wait(BAR(B_WKF)); } while (0)
#define TEST1(a) (hd ? 1u : mbar_test(a))
#define ZERO(pp, cond) do { if (!(cond)) { _Pragma("unroll") for (int i = 0; i < 16; i++) asm volatile("mov.b32 %0, 0;" : "=r"(pp[i])); } } while (0)
      constexpr uint32_t KB8 = 8 * B_KB, VB8 = 8 * B_VB;
      float u0[32], o[16];
      uint32_t pf2[16], pd2[16], ok;
      bool badA = false;
      mbar_wait(b0 + KB8);
      mbar_wait(b1 + KB8);
      TS(14);
      WG_FENCE();
      qk(u0, qa, k0);
      WG_COMMIT();
#pragma unroll
      for (int hd = 0; hd < 2; hd++) {
        const uint32_t (&q)[8] = hd ? qb : qa;
        const uint32_t ko = hd * 192, vo = hd * 256;
        float u1[32], u2[32], uf[32], ug[32], n0[32];
        uint32_t pa[16], pb[16], pc[16], pm[16];
        ok = TEST1(b2 + KB8) & TEST1(b0 + VB8);
        if (hd) WG_WAIT(1); else WG_WAIT(0);
        pin(u0);
        WG_FENCE();
        qk(u1, q, k1 + ko);
        WG_COMMIT();
        if (hd) { pv<1>(o, pf2, vf); pv<1>(o, pd2, vg); WG_COMMIT(); }
        exp_pack(u0, pa);
        pinu(pa);
        if (hd) BB(0); else if (!ok) { mbar_wait(b2 + KB8); mbar_wait(b0 + VB8); }
        ZERO(pa, p0);
        ok = TEST1(bf + KB8) & TEST1(bg + KB8) & TEST1(b1 + VB8);
        WG_WAIT(0);
        if (hd) {
          pin(o);
          badA = o_epilogue<1>(o, 0, op, epoch & 1, c, 4 + w);
          if (OPRE) { st_pkt(op + 256, ~epoch & 1, 0u, 0u, 0u); st_pkt(op + 384, ~epoch & 1, 0u, 0u, 0u); }
          TS(4);
        }
        pin(u1);
        WG_FENCE();
        qk(u2, q, k2 + ko);
        WG_COMMIT();
        pv<0>(o, pa, v0 + vo);
        WG_COMMIT();
        exp_pack(u1, pb);
        pinu(pb);
        if (hd) BB(1); else if (!ok) { mbar_wait(bf + KB8); mbar_wait(bg + KB8); mbar_wait(b1 + VB8); }
        ZERO(pb, p1);
        ok = TEST1(b2 + VB8);
        WG_WAIT(1);
        pin(u2);
        WG_FENCE();
        qk(uf, q, kf + ko);
        qk(ug, q, kg + ko);
        WG_COMMIT();
        pv<1>(o, pb, v1 + vo);
        WG_COMMIT();
        exp_pack(u2, pc);
        pinu(pc);
        if (hd) BB(2); else if (!ok) mbar_wait(b2 + VB8);
        ZERO(pc, p2);
        ok = TEST1(bf + VB8) & TEST1(bg + VB8);
        WG_WAIT(1);
        pin(uf); pin(ug);
        WG_FENCE();
        if (!hd) { qk(n0, qb, k0 + 192); WG_COMMIT(); }
        pv<1>(o, pc, v2 + vo);
        WG_COMMIT();
#pragma unroll
        for (int j = 0; j < 8; j++) {
          const int t = t0 - 8 * j;
          ug[4 * j] = t >= 0 ? ug[4 * j] : uf[4 * j];
          ug[4 * j + 1] = t >= 1 ? ug[4 * j + 1] : uf[4 * j + 1];
          ug[4 * j + 2] = t >= -8 ? ug[4 * j + 2] : uf[4 * j + 2];
          ug[4 * j + 3] = t >= -7 ? ug[4 * j + 3] : uf[4 * j + 3];
        }
        exp_pack(ug, pm);
#pragma unroll
        for (int j = 0; j < 8; j++) {
          pf2[2 * j] = pm[2 * j] & dm[j + 1];         pd2[2 * j] = pm[2 * j] & ~dm[j + 1];
          pf2[2 * j + 1] = pm[2 * j + 1] & dm[j];     pd2[2 * j + 1] = pm[2 * j + 1] & ~dm[j];
        }
        pinu(pf2); pinu(pd2);
        if (hd) BB(3); else if (!ok) { mbar_wait(bf + VB8); mbar_wait(bg + VB8); }
        ZERO(pf2, pf);
        if (!hd) {
#pragma unroll
          for (int i = 0; i < 32; i++) u0[i] = n0[i];
        }
      }
      WG_FENCE();
      pv<1>(o, pf2, vf + 256);
      pv<1>(o, pd2, vg + 256);
      WG_COMMIT();
#pragma unroll
      for (int i = 0; i < 8; i++) oq[i] = ld_pkt(ip + (i >> 1) * 1024 + (i & 1) * 128);
      WG_WAIT(0);
      pin(o);
      const bool badB = o_epilogue<1>(o, 1, op + 256, epoch & 1, c, 4 + w);
      TS(5);
      if (badA || badB) {
#pragma unroll 1
        for (int hd = 0; hd < 2; hd++) {
          if (!(hd ? badB : badA)) continue;
          uint32_t q[8];
#pragma unroll
          for (int i = 0; i < 8; i++) q[i] = hd ? qb[i] : qa[i];
          float m0 = -3.0e38f, m1 = -3.0e38f;
#pragma unroll
          for (int i = 0; i < 16; i++) o[i] = 0.f;
#pragma unroll 1
          for (int i = 4; i >= 0 && w + i >= lo; i--) {
            const int dmin = i == 4 ? 0 : -1000, dmax = i == 0 ? -1 : 1000;
            float s[32];
            uint32_t p[16];
            pinu(q);
            WG_FENCE();
            qk(s, q, kdb + (w + i) * 448 + hd * 192);
            WG_COMMIT();
            WG_WAIT(0);
            pin(s);
            float x0 = m0, x1 = m1;
#pragma unroll
            for (int j = 0; j < 32; j++) {
              const int d = t0 - 8 * (j >> 2) - (j & 1) + (j & 2) * 4;
              s[j] = (d >= dmin && d <= dmax) ? s[j] : __int_as_float(0xff800000);
              if (j & 2) x1 = fmaxf(x1, s[j]); else x0 = fmaxf(x0, s[j]);
            }
#pragma unroll
            for (int k = 1; k < 4; k <<= 1) {
              x0 = fmaxf(x0, __shfl_xor_sync(~0u, x0, k));
              x1 = fmaxf(x1, __shfl_xor_sync(~0u, x1, k));
            }
            const float al0 = ex2(m0 - x0), al1 = ex2(m1 - x1);
            m0 = x0; m1 = x1;
#pragma unroll
            for (int j = 0; j < 32; j++) s[j] -= (j & 2) ? m1 : m0;
            exp_pack(s, p);
#pragma unroll
            for (int j = 0; j < 16; j++) o[j] *= (j & 2) ? al1 : al0;
            pinu(p); pin(o);
            WG_FENCE();
            pv<1>(o, p, vdb + (w + i) * 512 + hd * 256);
            WG_COMMIT();
            WG_WAIT(0);
            pin(o);
          }
          o_epilogue<0>(o, hd, op + hd * 256, epoch & 1, c, 0);
        }
      }
      warp_arrive(BAR(B_ATD), lane);
    }

    uint32_t G1, G2;
    {
      float acc[56];
      const uint32_t d = dlo(sb + (w ? OFF_WV : OFF_WQ), 28672);
      mbar_wait(BAR(B_WOF + w));
#pragma unroll
      for (int hd = 0; hd < 2; hd++) {
        uint4 q[8];
        int n = 0;
        while (true) {
          uint32_t bad = 0;
#pragma unroll
          for (int i = 0; i < 8; i++) q[i] = (hd == 0 && n == 0) ? oq[i] : ld_pkt(ip + (i >> 1) * 1024 + hd * 256 + (i & 1) * 128);
#pragma unroll
          for (int i = 0; i < 8; i++) bad |= q[i].x ^ epoch;
          if (__all_sync(~0u, !(bad & 1))) break;
          spin_guard(n);
        }
        if (hd) warp_arrive(BAR(B_OGD), lane);
        WG_FENCE();
#pragma unroll
        for (int i = 0; i < 8; i++) {
          const uint32_t dd = d + (7 * (i >> 1) + 3 * hd + 2 * (i & 1)) * 64;
          if (hd == 0 && i == 0) wg112<0>(acc, q[i].x, q[i].y, q[i].z, q[i].w, dd);
          else wg112<1>(acc, q[i].x, q[i].y, q[i].z, q[i].w, dd);
        }
        WG_COMMIT();
        TS(6 + hd);
      }
      mbar_wait(BAR(B_ATD));
      mbar_wait(BAR(B_XRF));
      mbar_wait(BAR(B_SW));
      const int lrow = 16 * v + r + 8 * w, grp = rb * 2 + half, grow = grp * 64 + lrow;
      const uint32_t xr = sb + OFF_XR + lrow * 224 + 4 * c;
      uint32_t hh[14], ln[14], wr[14];
#pragma unroll
      for (int j = 0; j < 14; j++) { hh[j] = lds32(xr + 16 * j); wr[j] = lds32(sb + OFF_MISC + 256 + 16 * j + 4 * c); }
      WG_WAIT(0);
      pin(acc);
      const uint32_t ex = sb + OFF_EX + wt * 16;
#pragma unroll
      for (int j = 0; j < 7; j++) {
        if (w) sts128f(ex + 14336 + j * 2048, acc[8 * j], acc[8 * j + 1], acc[8 * j + 4], acc[8 * j + 5]);
        else sts128f(ex + j * 2048, acc[8 * j + 2], acc[8 * j + 3], acc[8 * j + 6], acc[8 * j + 7]);
      }
      bar_sync(1, 256);
      float s0 = 0.f, u0 = 0.f, d0 = 0.f;
#pragma unroll
      for (int j = 0; j < 7; j++) {
        const float4 y = lds128f(ex + (w ? 0 : 14336) + j * 2048);
        hh[2 * j] = hadd2(hh[2 * j], pack2((w ? acc[8 * j + 2] : acc[8 * j]) + y.x, (w ? acc[8 * j + 3] : acc[8 * j + 1]) + y.y));
        hh[2 * j + 1] = hadd2(hh[2 * j + 1], pack2((w ? acc[8 * j + 6] : acc[8 * j + 4]) + y.z, (w ? acc[8 * j + 7] : acc[8 * j + 5]) + y.w));
#pragma unroll
        for (int i = 0; i < 2; i++) {
          const float a0 = bf_lo(hh[2 * j + i]), a1 = bf_hi(hh[2 * j + i]);
          s0 += a0 + a1;
          u0 = fmaf(a0, a0, fmaf(a1, a1, u0));
          d0 = fmaf(a0, bf_lo(wr[2 * j + i]), fmaf(a1, bf_hi(wr[2 * j + i]), d0));
        }
      }
#pragma unroll
      for (int o = 1; o < 4; o <<= 1) {
        s0 += __shfl_xor_sync(~0u, s0, o); u0 += __shfl_xor_sync(~0u, u0, o); d0 += __shfl_xor_sync(~0u, d0, o);
      }
      uint4* sp = P.sc->st + grp * 256 + lrow;
      if (c == 0) st_pkt(sp + quart * 64, __float_as_uint(s0), __float_as_uint(u0), __float_as_uint(d0), epoch);
      TS(8);
      {
        int n = 0;
        while (true) {
          const uint4 q = ld_pkt(sp + c * 64);
          s0 = __uint_as_float(q.x); u0 = __uint_as_float(q.y); d0 = __uint_as_float(q.z);
          if (__all_sync(~0u, q.w == epoch)) break;
          spin_guard(n);
        }
      }
#pragma unroll
      for (int o = 1; o < 4; o <<= 1) {
        s0 += __shfl_xor_sync(~0u, s0, o); u0 += __shfl_xor_sync(~0u, u0, o); d0 += __shfl_xor_sync(~0u, d0, o);
      }
      const float mu = s0 * (1.f / D_), rs = ln_rstd(u0 * (1.f / D_) - mu * mu);
      const uint32_t mb = pack2(mu, mu);
      const uint32_t rr = pack2(0.f, (d0 - bf_lo(mb) * __uint_as_float(lds32(sb + OFF_MISC + 16))) * rs);
      const uint32_t key = (rr ^ (0x80000000u | (((int)rr >> 31) & 0x7fff0000u))) | (0xffffu - grow);
      const uint32_t k1 = __reduce_max_sync(~0u, key), k2 = __reduce_max_sync(~0u, key == k1 ? 0u : key);
      if (lane == 0) {
        sts32(sb + OFF_MISC + 64 + warp * 8, k1);
        sts32(sb + OFF_MISC + 68 + warp * 8, k2);
        mbar_arrive(BAR(B_KEY));
      }
#pragma unroll
      for (int j = 0; j < 14; j++) {
        const uint32_t t0 = hsub2(hh[j], mb);
        ln[j] = pack2(bf_lo(t0) * rs, bf_hi(t0) * rs);
      }
      mbar_wait(BAR(B_KEY));
      const uint32_t kk = lds32(sb + OFF_MISC + 64 + (lane & 15) * 4);
      G1 = __reduce_max_sync(~0u, kk);
      G2 = __reduce_max_sync(~0u, kk == G1 ? 0u : kk);
      if (quart == 0 && tid < 2) st_pkt(P.sc->top + grp * 2 + tid, G1, G2, 0u, epoch);
      if (tid == 0) mbar_arrive(BAR(B_E3D));
      TS(9);
      if (key == G1 || key == G2) {
        uint4* cp = P.sc->cand + (grow * 8 + 2 * quart) * 24 + c;
#pragma unroll
        for (int i = 0; i < 2; i++) {
          st_pkt(cp + 24 * i, ln[7 * i], ln[7 * i + 1], ln[7 * i + 2], epoch);
          st_pkt(cp + 24 * i + 4, ln[7 * i + 3], ln[7 * i + 4], ln[7 * i + 5], epoch);
          st_pkt(cp + 24 * i + 8, ln[7 * i + 6], 0u, 0u, epoch);
        }
#pragma unroll
        for (int i = 0; i < 2; i++) {
          st_pkt(cp + 24 * i + 12, hh[7 * i], hh[7 * i + 1], hh[7 * i + 2], epoch);
          st_pkt(cp + 24 * i + 16, hh[7 * i + 3], hh[7 * i + 4], hh[7 * i + 5], epoch);
          st_pkt(cp + 24 * i + 20, hh[7 * i + 6], 0u, 0u, epoch);
        }
      }
#pragma unroll
      for (int j = 0; j < 14; j++) sts32(xr + 16 * j, hadd2(hh[j], ln[j]));
      bar_sync(1, 256);
    }
    const int row0 = rb * 128 + half * 64;
    const int c1 = 0xffff - (G1 & 0xffffu) - row0, c2 = 0xffff - (G2 & 0xffffu) - row0;
    char* const obase = (char*)P.out + row0 * 896 + quart * 224;
#define OUT_STORES() _Pragma("unroll") for (int k = 0; k < 4; k++) { \
      const int i = tid + 256 * k, row = (i * 4682) >> 16;       \
      if (i < 896 && row != c1 && row != c2) *(uint4*)(obase + row * 672 + i * 16) = lds128(sb + OFF_XR + i * 16); }
    if (OUTAT == 0) { OUT_STORES() }
    TS(10);

    const bool ffn = bid < 112;
    uint32_t ag[14], au[14], ad[16];
    if (ffn) {
      mbar_wait(BAR(B_FFW));
      const uint32_t wa = sb + OFF_WG + (56 * warp + (lane & 7) + ((lane >> 4) & 1) * 8) * 32 + ((lane >> 3) & 1) * 16;
#pragma unroll
      for (int s = 0; s < 3; s++) {
        ldsm4t(ag[4 * s], ag[4 * s + 1], ag[4 * s + 2], ag[4 * s + 3], wa + s * 512);
        ldsm4t(au[4 * s], au[4 * s + 1], au[4 * s + 2], au[4 * s + 3], wa + 14336 + s * 512);
      }
      const uint32_t wb = sb + OFF_WG + (56 * warp + 48 + (lane & 7)) * 32 + ((lane >> 3) & 1) * 16;
      ldsm2t(ag[12], ag[13], wb);
      ldsm2t(au[12], au[13], wb + 14336);
      const uint32_t wc = sb + OFF_WD + ((lane & 7) + ((lane >> 4) & 1) * 8) * 896 + (56 * warp + ((lane >> 3) & 1) * 8) * 2;
#pragma unroll
      for (int m = 0; m < 4; m++) ldsm4t(ad[4 * m], ad[4 * m + 1], ad[4 * m + 2], ad[4 * m + 3], wc + m * 32);
    }
    mbar_wait(BAR(B_TOP));
    const uint32_t K1 = lds32(sb + OFF_MISC), K2 = lds32(sb + OFF_MISC + 4);
    TS(11);
    const bool fin = bid >= 96;
    const int fj = bid - 96, fr = (tid >> 2) & 7, fe = tid & 3;
    const int fcl = 16 * (fj & 3) + fr + 8 * (fe >> 1);
    const uint32_t fkey = (fe & 1) ? K2 : K1;
    const int frow = 0xffff - (fkey & 0xffffu);
    const bool fval = fin && tid < 32 && fcl < 56;
    if (ffn) {
      uint32_t b[7] = {0u, 0u, 0u, 0u, 0u, 0u, 0u};
      {
        const int row = 0xffff - (((lane & 4) ? K2 : K1) & 0xffffu);
        const uint4* cp = P.sc->cand + (row * 8 + warp) * 24 + c;
        int t0 = 0;
        while (true) {
          bool ok = true;
          if (lane < 8) {
            const uint4 q0 = ld_pkt(cp), q1 = ld_pkt(cp + 4), q2 = ld_pkt(cp + 8);
            ok = q0.w == epoch && q1.w == epoch && q2.w == epoch;
            b[0] = q0.x; b[1] = q0.y; b[2] = q0.z; b[3] = q1.x; b[4] = q1.y; b[5] = q1.z; b[6] = q2.x;
          }
          if (__all_sync(~0u, ok)) break;
          spin_guard(t0);
        }
      }
      float cg[4] = {0.f, 0.f, 0.f, 0.f}, cu[4] = {0.f, 0.f, 0.f, 0.f};
#pragma unroll
      for (int s = 0; s < 3; s++) {
        mma16816(cg, ag[4 * s], ag[4 * s + 1], ag[4 * s + 2], ag[4 * s + 3], b[2 * s], b[2 * s + 1]);
        mma16816(cu, au[4 * s], au[4 * s + 1], au[4 * s + 2], au[4 * s + 3], b[2 * s], b[2 * s + 1]);
      }
      mma1688(cg, ag[12], ag[13], b[6]);
      mma1688(cu, au[12], au[13], b[6]);
      const uint32_t red = sb + OFF_RED;
      if (c == 0) {
        sts64f(red + warp * 256 + r * 8, cg[0], cg[1]);
        sts64f(red + warp * 256 + 64 + r * 8, cg[2], cg[3]);
        sts64f(red + warp * 256 + 128 + r * 8, cu[0], cu[1]);
        sts64f(red + warp * 256 + 192 + r * 8, cu[2], cu[3]);
      }
      bar_sync(1, 256);
      float g = 0.f, u = 0.f;
      const uint32_t ra = red + (lane & 15) * 8 + (lane >> 4) * 4;
#pragma unroll
      for (int i = 0; i < 8; i++) {
        g += __uint_as_float(lds32(ra + i * 256));
        u += __uint_as_float(lds32(ra + i * 256 + 128));
      }
      g = bfr(g);
      const float act = bfr(bfr(g / (1.0f + __expf(-g))) * bfr(u));
      const int sl = (lane & 4) * 4 + 2 * c;
      const float x0 = __shfl_sync(~0u, act, sl), x1 = __shfl_sync(~0u, act, sl + 1);
      const float x2 = __shfl_sync(~0u, act, sl + 8), x3 = __shfl_sync(~0u, act, sl + 9);
      const uint32_t b0 = lane < 8 ? pack2(x0, x1) : 0u, b1 = lane < 8 ? pack2(x2, x3) : 0u;
      uint4* yp = P.sc->y + bid * 256 + warp * 32 + r;
#pragma unroll
      for (int m = 0; m < 4; m++) {
        float y[4] = {0.f, 0.f, 0.f, 0.f};
        mma16816(y, ad[4 * m], ad[4 * m + 1], ad[4 * m + 2], ad[4 * m + 3], b0, b1);
        if (c == 0)
          st_pkt(yp + m * 8, (__float_as_uint(y[0]) & ~1u) | (epoch & 1u), __float_as_uint(y[1]), __float_as_uint(y[2]), __float_as_uint(y[3]));
      }
    }
    TS(12);
    if (OUTAT == 1) { OUT_STORES() }
    if (tid < 28) {
      const uint32_t g = tid < 14 ? G1 : G2;
      const int row = tid < 14 ? c1 : c2, j = tid < 14 ? tid : tid - 14;
      if (g != K1 && g != K2) *(uint4*)(obase + row * 896 + j * 16) = lds128(sb + OFF_XR + row * 224 + j * 16);
    }
    if (fin) {
      float lnv = 0.f, hv = 0.f;
      int t0 = 0;
      if (fval) {
        const int tile = fcl >> 3;
        const uint4* cp = P.sc->cand + (frow * 8 + (fj >> 2)) * 24 + (tile / 3) * 4 + ((fcl & 7) >> 1);
        while (true) {
          const uint4 q0 = ld_pkt(cp), q1 = ld_pkt(cp + 12);
          const int sl = tile % 3;
          const uint32_t a = sl == 0 ? q0.x : sl == 1 ? q0.y : q0.z, bq = sl == 0 ? q1.x : sl == 1 ? q1.y : q1.z;
          lnv = (fcl & 1) ? bf_hi(a) : bf_lo(a);
          hv = (fcl & 1) ? bf_hi(bq) : bf_lo(bq);
          if (q0.w == epoch && q1.w == epoch) break;
          spin_guard(t0);
        }
      }
      __syncwarp();
      const uint4* yp = P.sc->y + (tid >> 3) * 256 + fj * 8 + (tid & 7);
      float y0, y1, y2, y3;
      while (true) {
        bool ok = true;
        y0 = y1 = y2 = y3 = 0.f;
#pragma unroll
        for (int i = 0; i < 4; i++) {
          if (i < 3 || tid < 128) {
            const uint4 q = ld_pkt(yp + i * 32 * 256);
            ok &= ((q.x ^ epoch) & 1u) == 0;
            y0 += __uint_as_float(q.x); y1 += __uint_as_float(q.y); y2 += __uint_as_float(q.z); y3 += __uint_as_float(q.w);
          }
        }
        if (__all_sync(~0u, ok)) break;
        spin_guard(t0);
      }
#pragma unroll
      for (int o = 8; o < 32; o <<= 1) {
        y0 += __shfl_xor_sync(~0u, y0, o); y1 += __shfl_xor_sync(~0u, y1, o);
        y2 += __shfl_xor_sync(~0u, y2, o); y3 += __shfl_xor_sync(~0u, y3, o);
      }
      const uint32_t red = sb + OFF_RED2;
      if (lane < 8) sts128f(red + warp * 128 + lane * 16, y0, y1, y2, y3);
      bar_sync(1, 256);
      if (fval) {
        float y = 0.f;
#pragma unroll
        for (int i = 0; i < 8; i++) y += __uint_as_float(lds32(red + i * 128 + tid * 4));
        const uint32_t ob = fkey >> 16;
        const float rv = __uint_as_float(((ob & 0x8000u) ? (ob ^ 0x8000u) : (~ob & 0xffffu)) << 16);
        const float sg = bfr(1.0f / (1.0f + __expf(-rv)));
        const float res = hv + bfr(lnv + bfr(bfr(y) * sg));
        P.out[frow * D_ + 56 * (fj >> 2) + fcl] = __float2bfloat16(res);
      }
    }
    TS(13);
  } else {
    asm volatile("setmaxnreg.dec.sync.aligned.u32 56;");
    const int t = tid - 256;
    const int aw = warp - 8;
    if (lane == 0) {
      mbar_init(BAR(B_XT) + 8 * aw, 1);
      asm volatile("fence.mbarrier_init.release.cluster;" ::: "memory");
      if (aw == 0) {
        mbar_expect(BAR(B_XT), 16384);
        tma2d(sb + OFF_X, &tm_x, 0, rb * 128, BAR(B_XT));
        TS(12);
      }
    }
    __syncwarp();
    bar_arrive(7, NTHR);
    bar_sync(3, 128);
    if (t == 0) {
#pragma unroll
      for (int i = 1; i < 7; i++) {
        if (i & 1) mbar_expect(BAR(B_XT + (i + 1) / 2), 32768);
        tma2d(sb + OFF_X + i * 16384, &tm_x, i * 64, rb * 128, BAR(B_XT + (i + 1) / 2));
      }
      TS(13);
    }
    bar_sync(0, NTHR);
    if (t == 0) {
      if (WKD) mbar_wait(BAR(B_XT + (WKD ? WKD - 1 : 0)));
#pragma unroll
      for (int i = 0; i < 4; i++) {
        if (!(i & 1)) mbar_expect(BAR(B_WKF + (i >> 1)), 28672);
        tma2d(sb + OFF_WK + i * 14336, &tm_w, 448 + wcol, i * 112, BAR(B_WKF + (i >> 1)));
      }
      TS(14);
    }
    if (t == 0) {
#pragma unroll
      for (int i = 0; i < 8; i++) st_pkt(P.sc->flag + (rb * 8 + hg) * 8 + i, 0u, 0u, 0u, 0u);
      TS(9);
      if (WVD) mbar_wait(BAR(B_WKF + (WVD ? WVD - 1 : 0)));
      mbar_expect(BAR(B_WVF), 57344);
#pragma unroll
      for (int i = 0; i < 4; i++) tma2d(sb + OFF_WV + i * 14336, &tm_w, 896 + wcol, i * 112, BAR(B_WVF));
      TS(10);
    }
    uint32_t epoch;
    asm volatile("ld.relaxed.gpu.global.u32 %0, [%1];" : "=r"(epoch) : "l"(&P.sc->epoch) : "memory");
    if (warp == 9) {
      float s = 0.f;
#pragma unroll
      for (int i = 0; i < 7; i++) {
        const int j = lane + 32 * i - quart * 56;
        const uint32_t u = __ldg((const uint32_t*)P.wr + lane + 32 * i);
        s += bf_lo(u) + bf_hi(u);
        if (j >= 0 && j < 56) sts32(sb + OFF_MISC + 256 + j * 4, u);
      }
#pragma unroll
      for (int o = 16; o; o >>= 1) s += __shfl_xor_sync(~0u, s, o);
      if (lane == 0) sts32(sb + OFF_MISC + 16, __float_as_uint(s));
      warp_arrive(BAR(B_SW), lane);
    }
    if (t == 0) {
      mbar_wait(BAR(B_XE));
      mbar_expect(BAR(B_WQF), 57344);
#pragma unroll
      for (int i = 0; i < 4; i++) tma2d(sb + OFF_WQ + i * 14336, &tm_w, wcol, i * 112, BAR(B_WQF));
      TS(11);
    }
    __syncwarp();
    epoch += 1;
    const uint32_t par = epoch & 1;
    uint4* const gp = P.sc->kv + (rb * 8 + hg) * 2048;
    const uint4* const g1 = gp - 8 * 2048;
    const uint4* const g2 = rb > 1 ? g1 - 8 * 2048 : g1;
#define IMG(n, slot) (sb + ((n) >= 2 ? OFF_VA + (slot) * 8192 : OFF_KA + (slot) * 7168))
#define FETCH(n) { \
      const uint32_t by = (n) >= 2 ? 8192 : 7168; \
      mbar_expect(BAR(B_FB) + 8 * (n), 2 * by); \
      bulk_g2s(IMG(n, 3 - ((n) & 1)), g1 + (n) * 512, by, BAR(B_FB) + 8 * (n)); \
      bulk_g2s(IMG(n, 1 - ((n) & 1)), g2 + (n) * 512, by, BAR(B_FB) + 8 * (n)); }
    uint4* const fl = P.sc->flag + (rb * 8 + hg) * 8;
    if (t == 0) {
#pragma unroll
      for (int n = 0; n < 4; n++) {
        mbar_wait(BAR((n >= 2 ? B_VB : B_KB) + 5 - (n & 1)));
        st_pkt(fl + 2 * n, 0u, 0u, 0u, epoch);
        bulk_s2g(gp + n * 512, IMG(n, 5 - (n & 1)), n >= 2 ? 8192 : 7168);
        TS(20 + n);
      }
      asm volatile("cp.async.bulk.commit_group;" ::: "memory");
    } else if (warp > 8 && rb) {
#pragma unroll 1
      for (int n = warp - 9; n < 4; n += 3) {
        if (lane < 2) {
          const uint4* fp = fl + 2 * n - ((lane && rb > 1) ? 128 : 64);
          int k = 0;
          while (ld_pkt(fp).w != epoch) spin_guard(k);
        }
        __syncwarp();
        { const uint32_t c0 = clock(); while ((uint32_t)clock() - c0 < FDELAY) {} }
        if (n == 2) mbar_wait(BAR(B_KPD));
        if (n == 0) mbar_wait(BAR(B_XE));
        const uint32_t lo = lane * 32 + (lane & 4) * 4, i1 = IMG(n, 3 - (n & 1)) + lo, i2 = IMG(n, 1 - (n & 1)) + lo;
        int tries = 0;
        while (true) {
          if (lane == 0) FETCH(n)
          mbar_wait_par(BAR(B_FB) + 8 * n, tries & 1);
          uint32_t bad = 0;
#pragma unroll
          for (int k = 0; k < 8; k++) {
            const uint32_t o = (k < 7 || n >= 2) ? k * 1024 : 0;
            bad |= (lds32(i1 + o) ^ par) | (lds32(i2 + o) ^ par);
          }
          if (__all_sync(~0u, !(bad & 1))) break;
          spin_guard(tries);
        }
        if (lane == 0) {
          const uint32_t hb = BAR(n >= 2 ? B_VB : B_KB) + 8 - 8 * (n & 1);
          mbar_arrive(hb + 16);
          mbar_arrive(hb);
        }
      }
    }
    if (t == 0) {
      mbar_wait(BAR(B_QPD));
      if (rb) mbar_wait(BAR(B_VB + 2));
#pragma unroll
      for (int i = 0; i < 2; i++) {
        mbar_expect(BAR(B_WOF + i), 57344);
        tma2d(sb + (i ? OFF_WV : OFF_WQ), &tm_wo, quart * 112, 224 * i, BAR(B_WOF + i));
        tma2d(sb + (i ? OFF_WV : OFF_WQ) + 28672, &tm_wo, quart * 112 + 64, 224 * i, BAR(B_WOF + i));
      }
      mbar_expect(BAR(B_XRF), 14336);
      tma2d(sb + OFF_XR, &tm_xr, quart * 112, rb * 128 + half * 64, BAR(B_XRF));
      l2_prefetch((const char*)P.wg + bid * 12544, 12544);
      l2_prefetch((const char*)P.wu + bid * 12544, 12544);
      l2_prefetch((const char*)P.wd + bid * 12544, 12544);
      if (bid < 112) {
        mbar_wait(BAR(FFAT == 0 ? B_ATD : FFAT == 1 ? B_OGD : B_E3D));
        mbar_expect(BAR(B_FFW), 43008);
        tma2d(sb + OFF_WG, &tm_g, bid * 16, 0, BAR(B_FFW));
        tma2d(sb + OFF_WG + 7168, &tm_g, bid * 16, 224, BAR(B_FFW));
        tma2d(sb + OFF_WU, &tm_u, bid * 16, 0, BAR(B_FFW));
        tma2d(sb + OFF_WU + 7168, &tm_u, bid * 16, 224, BAR(B_FFW));
        bulk_g2s(sb + OFF_WD, (const char*)P.wd + bid * 14336, 14336, BAR(B_FFW));
      }
      asm volatile("cp.async.bulk.wait_group 0;" ::: "memory");
    } else if (warp == 9) {
      mbar_wait(BAR(B_E3D));
      uint4 q;
      int n = 0;
      while (true) {
        q = ld_pkt(P.sc->top + lane * 2);
        if (__all_sync(~0u, q.w == epoch)) break;
        spin_guard(n);
      }
      const uint32_t K1 = __reduce_max_sync(~0u, q.x);
      const uint32_t K2 = __reduce_max_sync(~0u, q.x == K1 ? q.y : q.x);
      if (lane == 0) {
        sts32(sb + OFF_MISC, K1);
        sts32(sb + OFF_MISC + 4, K2);
        mbar_arrive(BAR(B_TOP));
        if (bid == 0) asm volatile("st.relaxed.gpu.global.u32 [%0], %1;" ::"l"(&P.sc->epoch), "r"(epoch) : "memory");
      }
    }
  }
  TS_DUMP();
#undef BAR
}

typedef CUresult (*EncodeFn)(CUtensorMap*, CUtensorMapDataType, cuuint32_t, void*, const cuuint64_t*, const cuuint64_t*,
                             const cuuint32_t*, const cuuint32_t*, CUtensorMapInterleave, CUtensorMapSwizzle,
                             CUtensorMapL2promotion, CUtensorMapFloatOOBfill);

void make_map(EncodeFn enc, CUtensorMap* m, const void* p, int cols, int rows, int bc, int br, CUtensorMapSwizzle sw) {
  cuuint64_t gd[2] = {(cuuint64_t)cols, (cuuint64_t)rows};
  cuuint64_t gs[1] = {(cuuint64_t)cols * 2};
  cuuint32_t bx[2] = {(cuuint32_t)bc, (cuuint32_t)br};
  cuuint32_t es[2] = {1, 1};
  enc(m, CU_TENSOR_MAP_DATA_TYPE_BFLOAT16, 2, (void*)p, gd, gs, bx, es, CU_TENSOR_MAP_INTERLEAVE_NONE, sw,
      CU_TENSOR_MAP_L2_PROMOTION_L2_128B, CU_TENSOR_MAP_FLOAT_OOB_FILL_NONE);
}

}

extern "C" void kernel_launch(void* const* d_in, const int* in_sizes, int n_in, void* d_out, int out_size) {
  (void)in_sizes; (void)n_in; (void)out_size;
  static EncodeFn enc = nullptr;
  static Scratch* scratch = nullptr;
  if (!enc) {
    void* fn = nullptr;
    cudaDriverEntryPointQueryResult qr;
    cudaGetDriverEntryPoint("cuTensorMapEncodeTiled", &fn, cudaEnableDefault, &qr);
    enc = (EncodeFn)fn;
    cudaGetSymbolAddress((void**)&scratch, g_scratch);
    cudaFuncSetAttribute(fused_kernel, cudaFuncAttributeMaxDynamicSharedMemorySize, SMEM_BYTES);
  }
  CUtensorMap tx, tw, two, txr, tg, tu;
  make_map(enc, &txr, d_in[0], D_, S_, 112, 64, CU_TENSOR_MAP_SWIZZLE_NONE);
  make_map(enc, &tx, d_in[0], D_, S_, 64, 128, CU_TENSOR_MAP_SWIZZLE_128B);
  make_map(enc, &tw, d_in[1], 3 * D_, D_, 64, 112, CU_TENSOR_MAP_SWIZZLE_128B);
  make_map(enc, &two, d_in[2], D_, D_, 64, 224, CU_TENSOR_MAP_SWIZZLE_128B);
  make_map(enc, &tg, d_in[5], F_, D_, 16, 224, CU_TENSOR_MAP_SWIZZLE_NONE);
  make_map(enc, &tu, d_in[6], F_, D_, 16, 224, CU_TENSOR_MAP_SWIZZLE_NONE);
  Params p;
  p.wqkv = (const __nv_bfloat16*)d_in[1];
  p.x = (const __nv_bfloat16*)d_in[0];
  p.wr = (const __nv_bfloat16*)d_in[4];
  p.wg = (const __nv_bfloat16*)d_in[5];
  p.wu = (const __nv_bfloat16*)d_in[6];
  p.wd = (const __nv_bfloat16*)d_in[7];
  p.out = (__nv_bfloat16*)d_out;
  p.sc = scratch;
  p.zero = 0;
  fused_kernel<<<NCTA, NTHR, SMEM_BYTES>>>(tx, tw, two, txr, tg, tu, p);
}
```

```cpp
#include <cuda_runtime.h>
#include <cuda_bf16.h>
#include <cuda.h>
#include <stdint.h>

namespace {

constexpr int D_ = 448, F_ = 1792, S_ = 2048;
constexpr int NCTA = 128, NTHR = 384;
#define FORCE_FALLBACK 0
#define MAPV 0
#define FFAT 1
#define GRP 8
#define SQC 4
#define KEEPBB 7
#define D2 0
#define D2L 0
#define D3 400
#define D4 0
#define D5 0
#define D5N 1200
#define G3 0
#define G4 0
#define G5 0
#define WDEPTH 5
#define QDEPTH WDEPTH

constexpr uint32_t OFF_WK = 0;
constexpr uint32_t OFF_X = 57344;
constexpr uint32_t OFF_KA = 57344;
constexpr uint32_t OFF_XR = 100352;
constexpr uint32_t OFF_WQ = 114688;
constexpr uint32_t OFF_WV = 172032;
constexpr uint32_t OFF_BAR = 229376;
constexpr uint32_t OFF_MISC = OFF_BAR + 512;
constexpr uint32_t SMEM_BYTES = 232448;
constexpr uint32_t OFF_VA = 0;
constexpr uint32_t OFF_EX = 0;
constexpr uint32_t OFF_RED = 28672;
constexpr uint32_t OFF_RED2 = 32768;
constexpr uint32_t OFF_WG = OFF_KA, OFF_WU = OFF_KA + 14336, OFF_WD = 36864;

enum { B_WKF = 0  , B_WVF = 4  , B_WQF = 8, B_WOF = 9  , B_FFW = 11, B_TOP = 12, B_SW = 13, B_XRF = 14,
       B_FB = 15  , B_KB = 19  , B_VB = 25  ,
       B_XE = 31, B_KPD = 32, B_QPD = 33, B_ATD = 34, B_OGD = 35, B_KEY = 36, B_FIN = 37,
       B_XT = 40   };

struct Scratch {
  uint4 kv[NCTA * 2 * 2 * 512];
  uint4 o[NCTA * 2 * 2 * 2 * 128];
  uint4 st[32 * 4 * 64];
  uint4 flag[NCTA * 8];
  uint4 top[32 * 2];
  uint4 cand[32 * 2 * 8 * 6 * 4];
  uint4 y[112 * 256];
  uint32_t epoch;
};
__device__ Scratch g_scratch;
#define TS(i)
#define TSV(i, val)
#define TSX(i)
#define TT(i)
#define TS_DUMP()

__device__ __forceinline__ void spin_guard(int& n) {
  if (++n > (1 << 21)) __trap();
}
__device__ __forceinline__ void mbar_arrive(uint32_t bar) {
  asm volatile("mbarrier.arrive.shared::cta.b64 _, [%0];" ::"r"(bar) : "memory");
}
__device__ __forceinline__ void mbar_wait(uint32_t bar) {
  asm volatile("{\n.reg .pred p;\n.reg .u32 n;\nmov.u32 n, 0;\nMW_LOOP:\n"
               "mbarrier.try_wait.parity.shared::cta.b64 p, [%0], 0;\n@p bra MW_DONE;\n"
               "add.u32 n, n, 1;\nsetp.lt.u32 p, n, 4194304;\n@p bra MW_LOOP;\ntrap;\nMW_DONE:\n}" ::"r"(bar) : "memory");
}
__device__ __forceinline__ void mbar_wait_par(uint32_t bar, uint32_t par) {
  asm volatile("{\n.reg .pred p;\n.reg .u32 n;\nmov.u32 n, 0;\nMW_LOOP:\n"
               "mbarrier.try_wait.parity.shared::cta.b64 p, [%0], %1;\n@p bra MW_DONE;\n"
               "add.u32 n, n, 1;\nsetp.lt.u32 p, n, 4194304;\n@p bra MW_LOOP;\ntrap;\nMW_DONE:\n}" ::"r"(bar), "r"(par) : "memory");
}
__device__ __forceinline__ uint32_t mbar_test(uint32_t bar) {
  uint32_t ok;
  asm volatile("{\n.reg .pred p;\nmbarrier.test_wait.parity.shared::cta.b64 p, [%1], 0;\nselp.u32 %0, 1, 0, p;\n}" : "=r"(ok) : "r"(bar) : "memory");
  return ok;
}
template <int N> __device__ __forceinline__ void pause() {
  if (N) { const uint32_t c0 = clock(); while ((uint32_t)clock() - c0 < N) {} }
}
__device__ __forceinline__ void warp_arrive(uint32_t bar, int lane) {
  __syncwarp();
  if (lane == 0) mbar_arrive(bar);
}
__device__ __forceinline__ void fence_async() { asm volatile("fence.proxy.async.shared::cta;" ::: "memory"); }
#define ELECT_ASM(body) "{\n.reg .pred pe;\nelect.sync _|pe, 0xffffffff;\n@pe " body "\n}"
__device__ __forceinline__ void mbar_init_e(uint32_t bar, uint32_t cnt) {
  asm volatile(ELECT_ASM("mbarrier.init.shared::cta.b64 [%0], %1;") ::"r"(bar), "r"(cnt) : "memory");
}
__device__ __forceinline__ void mbar_expect_e(uint32_t bar, uint32_t bytes) {
  asm volatile(ELECT_ASM("mbarrier.arrive.expect_tx.shared::cta.b64 _, [%0], %1;") ::"r"(bar), "r"(bytes) : "memory");
}
__device__ __forceinline__ void tma2d_e(uint32_t dst, const CUtensorMap* m, int c0, int c1, uint32_t bar) {
  asm volatile(ELECT_ASM("cp.async.bulk.tensor.2d.shared::cluster.global.mbarrier::complete_tx::bytes [%0], [%1, {%3, %4}], [%2];")
               ::"r"(dst), "l"(m), "r"(bar), "r"(c0), "r"(c1) : "memory");
}
__device__ __forceinline__ void bulk_g2s_e(uint32_t dst, const void* src, uint32_t bytes, uint32_t bar) {
  asm volatile(ELECT_ASM("cp.async.bulk.shared::cluster.global.mbarrier::complete_tx::bytes [%0], [%1], %2, [%3];")
               ::"r"(dst), "l"(src), "r"(bytes), "r"(bar) : "memory");
}
__device__ __forceinline__ void bulk_s2g_e(void* dst, uint32_t src, uint32_t bytes) {
  asm volatile(ELECT_ASM("cp.async.bulk.global.shared::cta.bulk_group [%0], [%1], %2;") ::"l"(dst), "r"(src), "r"(bytes) : "memory");
}
__device__ __forceinline__ void l2_prefetch_e(const void* p, uint32_t bytes) {
  asm volatile(ELECT_ASM("cp.async.bulk.prefetch.L2.global [%0], %1;") ::"l"(p), "r"(bytes) : "memory");
}
__device__ __forceinline__ void st_pkt(uint4* p, uint32_t a, uint32_t b, uint32_t c, uint32_t d) {
  asm volatile("st.relaxed.gpu.global.v4.u32 [%0], {%1, %2, %3, %4};" ::"l"(p), "r"(a), "r"(b), "r"(c), "r"(d) : "memory");
}
__device__ __forceinline__ uint4 ld_pkt(const uint4* p) {
  uint4 v;
  asm volatile("ld.relaxed.gpu.global.v4.u32 {%0, %1, %2, %3}, [%4];" : "=r"(v.x), "=r"(v.y), "=r"(v.z), "=r"(v.w) : "l"(p) : "memory");
  return v;
}
__device__ __forceinline__ void ldsm4(uint32_t& r0, uint32_t& r1, uint32_t& r2, uint32_t& r3, uint32_t a) {
  asm volatile("ldmatrix.sync.aligned.m8n8.x4.shared.b16 {%0,%1,%2,%3}, [%4];"
               : "=r"(r0), "=r"(r1), "=r"(r2), "=r"(r3) : "r"(a) : "memory");
}
__device__ __forceinline__ void ldsm4t(uint32_t& r0, uint32_t& r1, uint32_t& r2, uint32_t& r3, uint32_t a) {
  asm volatile("ldmatrix.sync.aligned.m8n8.x4.trans.shared.b16 {%0,%1,%2,%3}, [%4];"
               : "=r"(r0), "=r"(r1), "=r"(r2), "=r"(r3) : "r"(a) : "memory");
}
__device__ __forceinline__ void ldsm2t(uint32_t& r0, uint32_t& r1, uint32_t a) {
  asm volatile("ldmatrix.sync.aligned.m8n8.x2.trans.shared.b16 {%0,%1}, [%2];" : "=r"(r0), "=r"(r1) : "r"(a) : "memory");
}
__device__ __forceinline__ void stsm4(uint32_t a, uint32_t r0, uint32_t r1, uint32_t r2, uint32_t r3) {
  asm volatile("stmatrix.sync.aligned.m8n8.x4.shared.b16 [%0], {%1,%2,%3,%4};" ::"r"(a), "r"(r0), "r"(r1), "r"(r2), "r"(r3) : "memory");
}
__device__ __forceinline__ void stsm2(uint32_t a, uint32_t r0, uint32_t r1) {
  asm volatile("stmatrix.sync.aligned.m8n8.x2.shared.b16 [%0], {%1,%2};" ::"r"(a), "r"(r0), "r"(r1) : "memory");
}
__device__ __forceinline__ void mma16816(float (&c)[4], uint32_t a0, uint32_t a1, uint32_t a2, uint32_t a3, uint32_t b0, uint32_t b1) {
  asm volatile("mma.sync.aligned.m16n8k16.row.col.f32.bf16.bf16.f32 {%0,%1,%2,%3}, {%4,%5,%6,%7}, {%8,%9}, {%0,%1,%2,%3};"
               : "+f"(c[0]), "+f"(c[1]), "+f"(c[2]), "+f"(c[3]) : "r"(a0), "r"(a1), "r"(a2), "r"(a3), "r"(b0), "r"(b1));
}
__device__ __forceinline__ void mma1688(float (&c)[4], uint32_t a0, uint32_t a1, uint32_t b0) {
  asm volatile("mma.sync.aligned.m16n8k8.row.col.f32.bf16.bf16.f32 {%0,%1,%2,%3}, {%4,%5}, {%6}, {%0,%1,%2,%3};"
               : "+f"(c[0]), "+f"(c[1]), "+f"(c[2]), "+f"(c[3]) : "r"(a0), "r"(a1), "r"(b0));
}
__device__ __forceinline__ uint32_t pack2(float lo, float hi) {
  uint32_t r;
  asm("cvt.rn.bf16x2.f32 %0, %1, %2;" : "=r"(r) : "f"(hi), "f"(lo));
  return r;
}
__device__ __forceinline__ float bf_lo(uint32_t u) { return __uint_as_float(u << 16); }
__device__ __forceinline__ float bf_hi(uint32_t u) { return __uint_as_float(u & 0xffff0000u); }
__device__ __forceinline__ float bfr(float x) { return bf_lo(pack2(x, 0.f)); }
__device__ __forceinline__ uint32_t hsub2(uint32_t a, uint32_t b) {
  uint32_t r;
  asm("sub.rn.bf16x2 %0, %1, %2;" : "=r"(r) : "r"(a), "r"(b));
  return r;
}
__device__ __forceinline__ uint32_t hadd2(uint32_t a, uint32_t b) {
  uint32_t r;
  asm("add.rn.bf16x2 %0, %1, %2;" : "=r"(r) : "r"(a), "r"(b));
  return r;
}
__device__ __forceinline__ uint32_t hfma2(uint32_t a, uint32_t b, uint32_t c) {
  uint32_t r;
  asm("fma.rn.bf16x2 %0, %1, %2, %3;" : "=r"(r) : "r"(a), "r"(b), "r"(c));
  return r;
}
__device__ __forceinline__ uint32_t hmul2(uint32_t a, uint32_t b) {
  uint32_t r;
  asm("mul.rn.bf16x2 %0, %1, %2;" : "=r"(r) : "r"(a), "r"(b));
  return r;
}
__device__ __forceinline__ float ex2(float x) {
  float r;
  asm("ex2.approx.ftz.f32 %0, %1;" : "=f"(r) : "f"(x));
  return r;
}
__device__ __forceinline__ float rcp(float x) {
  float r;
  asm("rcp.approx.ftz.f32 %0, %1;" : "=f"(r) : "f"(x));
  return r;
}
__device__ __forceinline__ uint32_t lds32(uint32_t a) {
  uint32_t v;
  asm volatile("ld.shared.u32 %0, [%1];" : "=r"(v) : "r"(a) : "memory");
  return v;
}
__device__ __forceinline__ void sts32(uint32_t a, uint32_t v) { asm volatile("st.shared.u32 [%0], %1;" ::"r"(a), "r"(v) : "memory"); }
__device__ __forceinline__ void sts64f(uint32_t a, float x, float y) {
  asm volatile("st.shared.v2.f32 [%0], {%1,%2};" ::"r"(a), "f"(x), "f"(y) : "memory");
}
__device__ __forceinline__ float2 lds64f(uint32_t a) {
  float2 v;
  asm volatile("ld.shared.v2.f32 {%0,%1}, [%2];" : "=f"(v.x), "=f"(v.y) : "r"(a) : "memory");
  return v;
}
__device__ __forceinline__ float4 lds128f(uint32_t a) {
  float4 v;
  asm volatile("ld.shared.v4.f32 {%0,%1,%2,%3}, [%4];" : "=f"(v.x), "=f"(v.y), "=f"(v.z), "=f"(v.w) : "r"(a) : "memory");
  return v;
}
__device__ __forceinline__ uint4 lds128(uint32_t a) {
  uint4 v;
  asm volatile("ld.shared.v4.u32 {%0,%1,%2,%3}, [%4];" : "=r"(v.x), "=r"(v.y), "=r"(v.z), "=r"(v.w) : "r"(a) : "memory");
  return v;
}
__device__ __forceinline__ void sts128(uint32_t a, uint4 v) {
  asm volatile("st.shared.v4.u32 [%0], {%1,%2,%3,%4};" ::"r"(a), "r"(v.x), "r"(v.y), "r"(v.z), "r"(v.w) : "memory");
}
__device__ __forceinline__ void bar_sync(int id, int n) { asm volatile("bar.sync %0, %1;" ::"r"(id), "r"(n) : "memory"); }
__device__ __forceinline__ bool bar_or(int id, int n, bool v) {
  uint32_t r;
  asm volatile("{\n.reg .pred p, q;\nsetp.ne.u32 p, %3, 0;\nbar.red.or.pred q, %1, %2, p;\nselp.u32 %0, 1, 0, q;\n}"
               : "=r"(r) : "r"(id), "r"(n), "r"((uint32_t)v) : "memory");
  return r;
}
__device__ __forceinline__ void bar_arrive(int id, int n) { asm volatile("bar.arrive %0, %1;" ::"r"(id), "r"(n) : "memory"); }
__device__ __forceinline__ uint32_t dlo(uint32_t addr, uint32_t lbo) { return ((addr & 0x3FFFF) >> 4) | ((lbo >> 4) << 16); }
constexpr uint32_t HI_SW128 = 0x40000040u;
constexpr uint32_t HI_K = 8u;
constexpr uint32_t HI_V = 64u;
#define WG_FENCE() asm volatile("wgmma.fence.sync.aligned;" ::: "memory")
#define WG_COMMIT() asm volatile("wgmma.commit_group.sync.aligned;" ::: "memory")
#define WG_WAIT(n) asm volatile("wgmma.wait_group.sync.aligned " #n ";" ::: "memory")
template <int N> __device__ __forceinline__ void pin(float (&d)[N]) {
#pragma unroll
  for (int i = 0; i < N; i++) asm volatile("" : "+f"(d[i])::"memory");
}

#define R4(d, i) "+f"(d[i]), "+f"(d[i + 1]), "+f"(d[i + 2]), "+f"(d[i + 3])
template <int ACC> __device__ __forceinline__ void wg32(float (&d)[16], uint32_t a0, uint32_t a1, uint32_t a2, uint32_t a3, uint32_t b) {
  asm volatile("{\n.reg .b64 dsc;\nmov.b64 dsc, {%20, %21};\nwgmma.mma_async.sync.aligned.m64n32k16.f32.bf16.bf16 "
               "{%0,%1,%2,%3,%4,%5,%6,%7,%8,%9,%10,%11,%12,%13,%14,%15}, {%16,%17,%18,%19}, dsc, %22, 1, 1, 1;\n}"
               : R4(d, 0), R4(d, 4), R4(d, 8), R4(d, 12) : "r"(a0), "r"(a1), "r"(a2), "r"(a3), "r"(b), "n"(HI_V), "n"(ACC));
}
template <int ACC> __device__ __forceinline__ void wg56(float (&d)[28], uint32_t a0, uint32_t a1, uint32_t a2, uint32_t a3, uint32_t b) {
  asm volatile("{\n.reg .b64 dsc;\nmov.b64 dsc, {%32, %34};\nwgmma.mma_async.sync.aligned.m64n56k16.f32.bf16.bf16 "
               "{%0,%1,%2,%3,%4,%5,%6,%7,%8,%9,%10,%11,%12,%13,%14,%15,%16,%17,%18,%19,%20,%21,%22,%23,%24,%25,%26,%27}, "
               "{%28,%29,%30,%31}, dsc, %33, 1, 1, 1;\n}"
               : R4(d, 0), R4(d, 4), R4(d, 8), R4(d, 12), R4(d, 16), R4(d, 20), R4(d, 24)
               : "r"(a0), "r"(a1), "r"(a2), "r"(a3), "r"(b), "n"(ACC), "n"(HI_SW128));
}
template <int ACC> __device__ __forceinline__ void wg64(float (&d)[32], uint32_t a0, uint32_t a1, uint32_t a2, uint32_t a3, uint32_t b) {
  asm volatile("{\n.reg .b64 dsc;\nmov.b64 dsc, {%36, %38};\nwgmma.mma_async.sync.aligned.m64n64k16.f32.bf16.bf16 "
               "{%0,%1,%2,%3,%4,%5,%6,%7,%8,%9,%10,%11,%12,%13,%14,%15,%16,%17,%18,%19,%20,%21,%22,%23,%24,%25,%26,%27,%28,%29,%30,%31}, "
               "{%32,%33,%34,%35}, dsc, %37, 1, 1, 0;\n}"
               : R4(d, 0), R4(d, 4), R4(d, 8), R4(d, 12), R4(d, 16), R4(d, 20), R4(d, 24), R4(d, 28)
               : "r"(a0), "r"(a1), "r"(a2), "r"(a3), "r"(b), "n"(ACC), "n"(HI_K));
}
template <int ACC> __device__ __forceinline__ void wg112(float (&d)[56], uint32_t a0, uint32_t a1, uint32_t a2, uint32_t a3, uint32_t b) {
  asm volatile("{\n.reg .b64 dsc;\nmov.b64 dsc, {%60, %62};\nwgmma.mma_async.sync.aligned.m64n112k16.f32.bf16.bf16 "
               "{%0,%1,%2,%3,%4,%5,%6,%7,%8,%9,%10,%11,%12,%13,%14,%15,%16,%17,%18,%19,%20,%21,%22,%23,%24,%25,%26,%27,"
               "%28,%29,%30,%31,%32,%33,%34,%35,%36,%37,%38,%39,%40,%41,%42,%43,%44,%45,%46,%47,%48,%49,%50,%51,%52,%53,%54,%55}, "
               "{%56,%57,%58,%59}, dsc, %61, 1, 1, 1;\n}"
               : R4(d, 0), R4(d, 4), R4(d, 8), R4(d, 12), R4(d, 16), R4(d, 20), R4(d, 24), R4(d, 28), R4(d, 32), R4(d, 36),
                 R4(d, 40), R4(d, 44), R4(d, 48), R4(d, 52)
               : "r"(a0), "r"(a1), "r"(a2), "r"(a3), "r"(b), "n"(ACC), "n"(HI_SW128));
}

__device__ __forceinline__ float ln_rstd(float var) {
  float s;
  asm("sqrt.approx.ftz.f32 %0, %1;" : "=f"(s) : "f"(bfr(bfr(fmaxf(var, 0.f)) + 1e-5f)));
  return rcp(bfr(s));
}
template <int ISV>
__device__ __forceinline__ void kv_epilogue(const float (&acc)[28], float rs0, float rs1, uint32_t img, uint32_t bar, uint32_t par, int v, int lane) {
  uint32_t e[14];
#pragma unroll
  for (int j = 0; j < 7; j++) {
    e[2 * j] = pack2(acc[4 * j] * rs0, acc[4 * j + 1] * rs0);
    e[2 * j + 1] = pack2(acc[4 * j + 2] * rs1, acc[4 * j + 3] * rs1);
  }
  const uint32_t keep = (lane & 3) ? ~0u : ~1u, tag = (lane & 3) ? 0u : par, one = 0x3f803f80u | tag;
#pragma unroll
  for (int j = 0; j < 14; j++) e[j] = (e[j] & keep) | tag;
  const uint32_t a = img + (lane >> 4) * 1024 + (16 * v + (lane & 15)) * 16;
  stsm4(a, e[0], e[1], e[2], e[3]);
  if (ISV) {
    const bool hi = lane & 2;
    stsm4(a + 2048, e[4], e[5], hi ? one : e[6], hi ? one : e[7]);
    stsm4(a + 4096, hi ? e[6] : one, hi ? e[7] : one, e[8], e[9]);
    stsm4(a + 6144, e[10], e[11], e[12], e[13]);
  } else {
    stsm4(a + 2048, e[4], e[5], e[6], e[7]);
    stsm4(a + 4096, e[8], e[9], e[10], e[11]);
    stsm2(a + 6144, e[12], e[13]);
  }
  fence_async();
  warp_arrive(bar, lane);
}

constexpr float SC = 0.18898223650461361f * 1.4426950408889634f;

template <int N> __device__ __forceinline__ void pinu(uint32_t (&d)[N]) {
#pragma unroll
  for (int i = 0; i < N; i++) asm volatile("" : "+r"(d[i])::"memory");
}
__device__ __forceinline__ void exp_pack(const float (&s)[32], uint32_t (&p)[16]) {
#pragma unroll
  for (int i = 0; i < 16; i++) p[i] = pack2(ex2(s[2 * i]), ex2(s[2 * i + 1]));
}
__device__ __forceinline__ void qk(float (&s)[32], const uint32_t (&q)[8], uint32_t kd) {
  wg64<0>(s, q[0], q[1], q[2], q[3], kd);
  wg64<1>(s, q[4], q[5], q[6], q[7], kd + 128);
}
template <int ACC> __device__ __forceinline__ void pv(float (&o)[16], const uint32_t (&p)[16], uint32_t vd) {
  wg32<ACC>(o, p[0], p[1], p[2], p[3], vd);
#pragma unroll
  for (int k = 1; k < 4; k++) wg32<1>(o, p[4 * k], p[4 * k + 1], p[4 * k + 2], p[4 * k + 3], vd + 16 * k);
}
template <int CHECK> __device__ __forceinline__ bool o_epilogue(const float (&o)[16], int hd, bool swap, uint4* op, uint32_t par, int c) {
  const bool pad = hd ? c < 2 : c >= 2;
  const float z0 = hd ? o[1] : o[12], z1 = hd ? o[3] : o[14];
  const float y0 = __shfl_xor_sync(~0u, z0, 2), y1 = __shfl_xor_sync(~0u, z1, 2);
  const float l0 = pad ? z0 : y0, l1 = pad ? z1 : y1;
  const float i0 = rcp(l0), i1 = rcp(l1);
  uint32_t e[8];
#pragma unroll
  for (int j = 0; j < 4; j++) {
    e[2 * j] = pack2(o[4 * j] * i0, o[4 * j + 1] * i0);
    e[2 * j + 1] = pack2(o[4 * j + 2] * i1, o[4 * j + 3] * i1);
  }
  if (pad && hd) { e[0] = 0; e[1] = 0; }
  if (pad && !hd) { e[6] = 0; e[7] = 0; }
  const float LO = 9.094947e-13f, HI = 1.0995116e12f;
  const bool bad = CHECK && __any_sync(~0u, FORCE_FALLBACK || !(l0 >= LO && l0 <= HI && l1 >= LO && l1 <= HI));
  if (swap) {
#pragma unroll
    for (int j = 0; j < 4; j++) { const uint32_t x = e[2 * j]; e[2 * j] = e[2 * j + 1]; e[2 * j + 1] = x; }
  }
  if (!bad) {
    st_pkt(op, (e[0] & ~1u) | par, e[1], e[2], e[3]);
    st_pkt(op + 128, (e[4] & ~1u) | par, e[5], e[6], e[7]);
  }
  return bad;
}

__device__ __forceinline__ void global_top2(const uint4* tp, uint32_t epoch, uint32_t& K1, uint32_t& K2, uint32_t& slot1, uint32_t& slot2) {
  pause<D4>();
  uint4 q = ld_pkt(tp);
  int n = 0;
  while (!__all_sync(~0u, (q.w ^ q.z) == epoch)) {
    spin_guard(n);
    pause<G4>();
    if ((q.w ^ q.z) != epoch) q = ld_pkt(tp);
  }
  K1 = __reduce_max_sync(~0u, q.x);
  K2 = __reduce_max_sync(~0u, q.x == K1 ? q.y : q.x);
  const uint32_t g1 = (~K1 & 0xffffu) >> 6, g2 = (~K2 & 0xffffu) >> 6;
  slot1 = g1 * 2;
  slot2 = g2 * 2 + (g1 == g2);
}

struct Params {
  const __nv_bfloat16* x; const __nv_bfloat16* wqkv; const __nv_bfloat16* wr;
  const __nv_bfloat16* wg; const __nv_bfloat16* wu; const __nv_bfloat16* wd;
  __nv_bfloat16* out;
  Scratch* sc;
  uint32_t zero;
};

__global__ void __launch_bounds__(NTHR, 1)
fused_kernel(const Params P, const __grid_constant__ CUtensorMap tm_x, const __grid_constant__ CUtensorMap tm_w, const __grid_constant__ CUtensorMap tm_wo,
             const __grid_constant__ CUtensorMap tm_xr,
             const __grid_constant__ CUtensorMap tm_g, const __grid_constant__ CUtensorMap tm_u) {
  extern __shared__ __align__(1024) unsigned char smem_raw[];
  const uint32_t sb = (uint32_t)__cvta_generic_to_shared(smem_raw);
  const uint32_t bars = sb + OFF_BAR;
#define BAR(i) (bars + 8 * (i))
  const int tid = threadIdx.x, warp = __shfl_sync(~0u, tid >> 5, 0), lane = tid & 31;
  const int bid = blockIdx.x;
  const int rb = (bid >> 5) * 4 + ((bid >> 2) & 3), hg = ((bid >> 4) & 1) * 4 + (bid & 3);
  const int half = hg >> 2, quart = hg & 3;

  const int wcol = ((hg * 112) & ~31) >> 1;
  if (warp < 8) {
    {
#pragma unroll
      for (int k = 0; k < 5; k++) {
        const int i = k * 8 + warp;
        if (i <= B_FIN) mbar_init_e(BAR(i), i >= B_XE ? 8 : i == B_VB + 4 ? 5 : (i == B_VB + 5 || i == B_KB + 4 || i == B_KB + 5) ? 4 : i == B_SW ? 3 : 1);
      }
      asm volatile("fence.mbarrier_init.release.cluster;" ::: "memory");
    }
    __syncwarp();
    bar_arrive(0, NTHR);
    asm volatile("setmaxnreg.inc.sync.aligned.u32 224;");
    uint32_t epoch;
    asm volatile("ld.relaxed.gpu.global.u32 %0, [%1];" : "=r"(epoch) : "l"(&P.sc->epoch) : "memory");
    const int w = warp >> 2, v = warp & 3, r = lane >> 2, c = lane & 3, wt = tid & 127;
    uint32_t qa[8], qb[8], dm[9], k0, k1, k2, kf, kg, v0, v1, v2, vf, vg, b0, b1, b2, bf, bg;
    const int lo = 4 - 2 * rb;
    const int s0 = 3 + w, s1 = 1 + 2 * w, s2 = 2, sf = w, sd = w + 4;
    const bool p0 = s0 >= lo, p1 = s1 >= lo, p2 = s2 >= lo, pf = sf >= lo;
    const uint32_t kdb = dlo(sb + OFF_KA, 1024), vdb = dlo(sb + OFF_VA, 128);
    const int t0 = 16 * v + r - 2 * c;
    {
      {
        const int e0 = p0 ? s0 : 4, e1 = p1 ? s1 : 4, e2 = p2 ? s2 : 4, ef = pf ? sf : 4;
#define UNI(x) __shfl_sync(~0u, (uint32_t)(x), 0)
        k0 = UNI(kdb + e0 * 448); k1 = UNI(kdb + e1 * 448); k2 = UNI(kdb + e2 * 448); kf = UNI(kdb + ef * 448); kg = UNI(kdb + sd * 448);
        v0 = UNI(vdb + (p0 ? s0 : 6) * 512); v1 = UNI(vdb + (p1 ? s1 : 6) * 512); v2 = UNI(vdb + (p2 ? s2 : 6) * 512);
        vf = UNI(vdb + (pf ? sf : 6) * 512); vg = UNI(vdb + sd * 512);
        b0 = UNI(BAR(e0)); b1 = UNI(BAR(e1)); b2 = UNI(BAR(e2)); bf = UNI(BAR(ef)); bg = UNI(BAR(sd));
#pragma unroll
        for (int j = 0; j < 9; j++) asm volatile("shl.b32 %0, %1, %2;" : "=r"(dm[j]) : "r"(0xffffffffu), "r"(max(0, 16 * (t0 + 9 - 8 * j))));
      }
      uint32_t a[112], mb0, mb1;
      float mu0, mu1, rs0, rs1, q0, q1;
      const uint32_t xa = sb + OFF_X + w * 8192 + (16 * v + (lane & 15)) * 128;
      {
        float su[2][4] = {};
        float sq[2][4] = {};
        bar_sync(7, NTHR);
#pragma unroll
        for (int kc = 0; kc < 7; kc++) {
          if (kc == 0 || (kc & 1)) { mbar_wait(BAR(B_XT + (kc + 1) / 2)); }
#pragma unroll
          for (int s = 0; s < 4; s++) {
            const int i = 16 * kc + 4 * s;
            ldsm4(a[i], a[i + 1], a[i + 2], a[i + 3], xa + kc * 16384 + (((2 * s + (lane >> 4)) ^ (lane & 7)) << 4));
          }
#pragma unroll
          for (int s = 0; s < 4; s++) {
            const int i = 16 * kc + 4 * s;
            mma16816(su[s & 1], a[i], a[i + 1], a[i + 2], a[i + 3], 0x3f803f80u, 0x3f803f80u);
          }
#pragma unroll
          for (int s = 0; s < 4; s += SQC) {
            uint32_t z[4];
#pragma unroll
            for (int j = 0; j < 4; j++) {
              const int i = 16 * kc + 4 * s + j;
              z[j] = hmul2(a[i], a[i]);
#pragma unroll
              for (int k = 1; k < SQC; k++) z[j] = hfma2(a[i + 4 * k], a[i + 4 * k], z[j]);
            }
            mma16816(sq[(kc + s / SQC) & 1], z[0], z[1], z[2], z[3], 0x3f803f80u, 0x3f803f80u);
          }
        }
        warp_arrive(BAR(B_XE), lane);
        TS(0);
        mu0 = (su[0][0] + su[1][0]) * (1.f / D_); mu1 = (su[0][2] + su[1][2]) * (1.f / D_);
        mb0 = pack2(mu0, mu0); mb1 = pack2(mu1, mu1);
#pragma unroll
        for (int i = 0; i < 112; i++) a[i] = hsub2(a[i], (i & 1) ? mb1 : mb0);
        q0 = (sq[0][0] + sq[1][0]) * (1.f / D_) - mu0 * mu0;
        q1 = (sq[0][2] + sq[1][2]) * (1.f / D_) - mu1 * mu1;
        if (__any_sync(~0u, !(mu0 * mu0 <= 16.f * q0 && mu1 * mu1 <= 16.f * q1))) {
          float g0[4] = {}, g1[4] = {};
#pragma unroll
          for (int i = 0; i < 112; i += 4) {
            mma16816(g0, a[i], a[i + 1], a[i + 2], a[i + 3], a[i], a[i + 2]);
            mma16816(g1, a[i], a[i + 1], a[i + 2], a[i + 3], a[i + 1], a[i + 3]);
          }
          q0 = __shfl_sync(~0u, (r & 1) ? g0[1] : g0[0], (lane & ~3) | (r >> 1));
          q1 = __shfl_sync(~0u, (r & 1) ? g1[3] : g1[2], (lane & ~3) | (r >> 1));
          const float d0 = mu0 - bf_lo(mb0), d1 = mu1 - bf_lo(mb1);
          q0 = q0 * (1.f / D_) - d0 * d0;
          q1 = q1 * (1.f / D_) - d1 * d1;
        }
        pinu(a);
      }
      epoch += 1;

      const uint32_t wofs = (hg & 1) * 16;
      float acc[28];
      {
        if (w == 0) bar_sync(1, 256);
        const uint32_t d = dlo(sb + OFF_WK + wofs, 16);
#pragma unroll
        for (int kc = 0; kc < 2; kc++) {
          mbar_wait(BAR(B_WKF + 2 * kc));
          mbar_wait(BAR(B_WKF + 2 * kc + 1));
          WG_FENCE();
#pragma unroll
          for (int s = 0; s < 14; s++) {
            const int k = 14 * kc + s;
            if (k == 0) wg56<0>(acc, a[0], a[1], a[2], a[3], d);
            else wg56<1>(acc, a[4 * k], a[4 * k + 1], a[4 * k + 2], a[4 * k + 3], d + 128 * k);
          }
        }
        WG_COMMIT();
        bar_arrive(2 - w, 256);
        rs0 = ln_rstd(q0);
        rs1 = ln_rstd(q1);
        WG_WAIT(0);
        pin(acc);
        TS(1);
        warp_arrive(BAR(B_KPD), lane);
        mbar_wait(BAR(B_XE));
        kv_epilogue<0>(acc, rs0, rs1, sb + OFF_KA + (4 + w) * 7168, BAR(B_KB + 4 + w), epoch & 1, v, lane);
      }
      {
        const uint32_t d = dlo(sb + OFF_WV + wofs, 16);
#pragma unroll
        for (int i = 0; i < 4; i++) mbar_wait(BAR(B_WVF + i));
        bar_sync(1 + w, 256);
        WG_FENCE();
#pragma unroll
        for (int k = 0; k < 28; k++) {
          if (k == 0) wg56<0>(acc, a[0], a[1], a[2], a[3], d);
          else wg56<1>(acc, a[4 * k], a[4 * k + 1], a[4 * k + 2], a[4 * k + 3], d + 128 * k);
        }
        WG_COMMIT();
        bar_arrive(2 - w, 256);
        WG_WAIT(0);
        pin(acc);
        TS(2);
        mbar_wait(BAR(B_KPD));
        kv_epilogue<1>(acc, rs0, rs1, sb + OFF_VA + (4 + w) * 8192, BAR(B_VB + 4 + w), epoch & 1, v, lane);
      }
      {
        const uint32_t d = dlo(sb + OFF_WQ + wofs, 16);
        mbar_wait(BAR(B_WQF));
        bar_sync(1 + w, 256);
        WG_FENCE();
#pragma unroll
        for (int k = 0; k < 28; k++) {
          if (k == 0) wg56<0>(acc, a[0], a[1], a[2], a[3], d);
          else wg56<1>(acc, a[4 * k], a[4 * k + 1], a[4 * k + 2], a[4 * k + 3], d + 128 * k);
        }
        WG_COMMIT();
        if (w == 1) bar_arrive(1, 256);
        WG_WAIT(0);
        pin(acc);
        TS(3);
        warp_arrive(BAR(B_QPD), lane);
        uint32_t e[14];
        const float rq0 = rs0 * SC, rq1 = rs1 * SC;
#pragma unroll
        for (int j = 0; j < 7; j++) {
          e[2 * j] = pack2(acc[4 * j] * rq0, acc[4 * j + 1] * rq0);
          e[2 * j + 1] = pack2(acc[4 * j + 2] * rq1, acc[4 * j + 3] * rq1);
        }
#pragma unroll
        for (int i = 0; i < 6; i++) { qa[i] = e[i]; qb[2 + i] = e[8 + i]; }
        qa[6] = c < 2 ? e[6] : 0u; qa[7] = c < 2 ? e[7] : 0u;
        qb[0] = c < 2 ? 0u : e[6]; qb[1] = c < 2 ? 0u : e[7];
      }
    }

    const uint4* ip = P.sc->o + ((rb * 8 + 4 * w) * 2 + half) * 512 + wt;
    uint4 oq[8];
    {
      uint4* op = P.sc->o + ((rb * 8 + hg) * 2 + w) * 512 + wt;
#define BB(k) do { if (P.zero & (1u << (k))) mbar_wait(BAR(B_WKF)); } while (0)
      constexpr uint32_t KB8 = 8 * B_KB, VB8 = 8 * B_VB;
      float o[16], ob[16];
      uint32_t ok;
      bool badA;
#define MERGE(g, f) _Pragma("unroll") for (int j = 0; j < 8; j++) { \
          const int t = t0 - 8 * j; \
          g[4 * j] = t >= 0 ? g[4 * j] : f[4 * j]; \
          g[4 * j + 1] = t >= 1 ? g[4 * j + 1] : f[4 * j + 1]; \
          g[4 * j + 2] = t >= -8 ? g[4 * j + 2] : f[4 * j + 2]; \
          g[4 * j + 3] = t >= -7 ? g[4 * j + 3] : f[4 * j + 3]; }
#define SPLIT(pm, pf2, pd2) _Pragma("unroll") for (int j = 0; j < 8; j++) { \
          pf2[2 * j] = pm[2 * j] & dm[j + 1];         pd2[2 * j] = pm[2 * j] & ~dm[j + 1]; \
          pf2[2 * j + 1] = pm[2 * j + 1] & dm[j];     pd2[2 * j + 1] = pm[2 * j + 1] & ~dm[j]; }
      float a0[32], c0[32], a1[32], a2[32], af[32], ag[32], c1[32], c2[32], cf[32], cg[32];
      uint32_t pa0[16], pb0[16], pa1[16], pa2[16], pam[16], paf[16], pad[16], pb1[16], pb2[16], pbm[16], pf2[16], pd2[16];
      mbar_wait(b0 + KB8);
      TS(14);
      WG_FENCE();
      qk(a0, qa, k0);
      WG_COMMIT();
      ok = mbar_test(b1 + KB8) & mbar_test(b0 + VB8);
      WG_WAIT(0);
      pin(a0);
      WG_FENCE();
      qk(c0, qb, k0 + 192);
      WG_COMMIT();
      exp_pack(a0, pa0);
#pragma unroll
      for (int i = 0; i < 4; i++) st_pkt(op + 128 * i, ~epoch & 1, 0u, 0u, 0u);
      pinu(pa0);
      if (!ok) { mbar_wait(b1 + KB8); mbar_wait(b0 + VB8); }
      ok = mbar_test(bf + KB8) & mbar_test(bg + KB8);
      WG_WAIT(0);
      pin(c0);
      WG_FENCE();
      qk(a1, qa, k1);
      WG_COMMIT();
      pv<0>(o, pa0, v0);
      WG_COMMIT();
      exp_pack(c0, pb0);
      pinu(pb0);
      if (!ok) { mbar_wait(bf + KB8); mbar_wait(bg + KB8); }
      ok = mbar_test(b2 + KB8) & mbar_test(b1 + VB8);
      WG_WAIT(0);
      pin(a1); pin(o);
      WG_FENCE();
      qk(af, qa, kf);
      qk(ag, qa, kg);
      WG_COMMIT();
      pv<0>(ob, pb0, v0 + 256);
      WG_COMMIT();
      exp_pack(a1, pa1);
      pinu(pa1);
      if (!ok) { mbar_wait(b2 + KB8); mbar_wait(b1 + VB8); }
      ok = mbar_test(bf + VB8) & mbar_test(bg + VB8);
      WG_WAIT(1);
      pin(af); pin(ag);
      WG_FENCE();
      qk(a2, qa, k2);
      WG_COMMIT();
      pv<1>(o, pa1, v1);
      WG_COMMIT();
      MERGE(ag, af)
      exp_pack(ag, pam);
      SPLIT(pam, paf, pad)
      pinu(paf); pinu(pad);
      if (!ok) { mbar_wait(bf + VB8); mbar_wait(bg + VB8); }
      ok = mbar_test(b2 + VB8);
      WG_WAIT(1);
      pin(a2);
      WG_FENCE();
      qk(c1, qb, k1 + 192);
      WG_COMMIT();
      pv<1>(o, paf, vf);
      pv<1>(o, pad, vg);
      WG_COMMIT();
      exp_pack(a2, pa2);
      pinu(pa2);
      if (!ok) mbar_wait(b2 + VB8);
      WG_WAIT(0);
      pin(c1); pin(o);
      WG_FENCE();
      qk(cf, qb, kf + 192);
      qk(cg, qb, kg + 192);
      WG_COMMIT();
      pv<1>(o, pa2, v2);
      WG_COMMIT();
      exp_pack(c1, pb1);
      pinu(pb1);
      if (KEEPBB & 1) BB(0);
      WG_WAIT(0);
      pin(cf); pin(cg); pin(o);
      badA = o_epilogue<1>(o, 0, half, op, epoch & 1, c);
      TS(4);
      WG_FENCE();
      qk(c2, qb, k2 + 192);
      WG_COMMIT();
      pv<1>(ob, pb1, v1 + 256);
      WG_COMMIT();
      MERGE(cg, cf)
      exp_pack(cg, pbm);
      SPLIT(pbm, pf2, pd2)
      pinu(pf2); pinu(pd2);
      if (KEEPBB & 2) BB(1);
      WG_WAIT(1);
      pin(c2);
      WG_FENCE();
      pv<1>(ob, pf2, vf + 256);
      pv<1>(ob, pd2, vg + 256);
      WG_COMMIT();
      exp_pack(c2, pb2);
      pinu(pb2);
      if (KEEPBB & 4) BB(2);
      WG_FENCE();
      pv<1>(ob, pb2, v2 + 256);
      WG_COMMIT();
#pragma unroll
      for (int i = 0; i < 8; i++) oq[i] = ld_pkt(ip + (i >> 1) * 1024 + (i & 1) * 128);
      WG_WAIT(0);
      pin(ob);
      const bool badB = o_epilogue<1>(ob, 1, half, op + 256, epoch & 1, c);
      TS(5);
      if (bar_or(4 + w, 128, badA || badB)) {
#pragma unroll 1
        for (int hd = 0; hd < 2; hd++) {
          if (!bar_or(4 + w, 128, hd ? badB : badA)) continue;
          uint32_t q[8];
#pragma unroll
          for (int i = 0; i < 8; i++) q[i] = hd ? qb[i] : qa[i];
          float m0 = -3.0e38f, m1 = -3.0e38f;
#pragma unroll
          for (int i = 0; i < 16; i++) o[i] = 0.f;
#pragma unroll 1
          for (int i = 4; i >= 0 && w + i >= lo; i--) {
            const int dmin = i == 4 ? 0 : -1000, dmax = i == 0 ? -1 : 1000;
            float s[32];
            uint32_t p[16];
            pinu(q);
            WG_FENCE();
            qk(s, q, kdb + (w + i) * 448 + hd * 192);
            WG_COMMIT();
            WG_WAIT(0);
            pin(s);
            float x0 = m0, x1 = m1;
#pragma unroll
            for (int j = 0; j < 32; j++) {
              const int d = t0 - 8 * (j >> 2) - (j & 1) + (j & 2) * 4;
              s[j] = (d >= dmin && d <= dmax) ? s[j] : __int_as_float(0xff800000);
              if (j & 2) x1 = fmaxf(x1, s[j]); else x0 = fmaxf(x0, s[j]);
            }
#pragma unroll
            for (int k = 1; k < 4; k <<= 1) {
              x0 = fmaxf(x0, __shfl_xor_sync(~0u, x0, k));
              x1 = fmaxf(x1, __shfl_xor_sync(~0u, x1, k));
            }
            const float al0 = ex2(m0 - x0), al1 = ex2(m1 - x1);
            m0 = x0; m1 = x1;
#pragma unroll
            for (int j = 0; j < 32; j++) s[j] -= (j & 2) ? m1 : m0;
            exp_pack(s, p);
#pragma unroll
            for (int j = 0; j < 16; j++) o[j] *= (j & 2) ? al1 : al0;
            pinu(p); pin(o);
            WG_FENCE();
            pv<1>(o, p, vdb + (w + i) * 512 + hd * 256);
            WG_COMMIT();
            WG_WAIT(0);
            pin(o);
          }
          o_epilogue<0>(o, hd, half, op + hd * 256, epoch & 1, c);
        }
      }
      warp_arrive(BAR(B_ATD), lane);
    }

    uint32_t G1, G2;
    {
      float acc[56];
      const uint32_t d = dlo(sb + (w ? OFF_WV : OFF_WQ), 28672);
      const int lrow = 16 * v + r + 8 * w, grp = rb * 2 + half, grow = grp * 64 + lrow;
      const uint32_t xr = sb + OFF_XR + lrow * 224 + 4 * c;
      mbar_wait(BAR(B_XRF));
#pragma unroll
      for (int j = 0; j < 14; j++) {
        const uint32_t x = lds32(xr + 16 * j);
        acc[4 * j] = bf_lo(x); acc[4 * j + 1] = bf_hi(x); acc[4 * j + 2] = 0.f; acc[4 * j + 3] = 0.f;
      }
      pin(acc);
      mbar_wait(BAR(B_WOF + w));
#pragma unroll
      for (int hd = 0; hd < 2; hd++) {
        uint4 q[8];
        if (hd && !half) { if (w) pause<D2L>(); else pause<D2>(); }
#pragma unroll
        for (int i = 0; i < 8; i++) q[i] = hd ? ld_pkt(ip + (i >> 1) * 1024 + 256 + (i & 1) * 128) : oq[i];
#pragma unroll
        for (int g = 0; g < 8; g += GRP) {
          int n = 0;
          while (true) {
            uint32_t bad = 0;
#pragma unroll
            for (int i = g; i < g + GRP; i++) bad |= q[i].x ^ epoch;
            if (__all_sync(~0u, !(bad & 1))) break;
            spin_guard(n);
#pragma unroll
            for (int i = g; i < g + GRP; i++) q[i] = ld_pkt(ip + (i >> 1) * 1024 + hd * 256 + (i & 1) * 128);
          }
          if (hd && g + GRP == 8) { warp_arrive(BAR(B_OGD), lane); TT(15); }
          WG_FENCE();
#pragma unroll
          for (int i = g; i < g + GRP; i++) wg112<1>(acc, q[i].x, q[i].y, q[i].z, q[i].w, d + (7 * (i >> 1) + 3 * hd + 2 * (i & 1)) * 64);
        }
        WG_COMMIT();
        TS(6 + hd);
      }
      mbar_wait(BAR(B_SW));
      uint32_t hh[14], ln[14], bw[14];
      const uint32_t bwa = sb + OFF_MISC + (r ? 256 : 512) + 4 * c;
#pragma unroll
      for (int j = 0; j < 14; j++) bw[j] = lds32(bwa + 16 * j);
      const float sw = __uint_as_float(lds32(sb + OFF_MISC + 16));
      uint4* sp = P.sc->st + grp * 256 + lrow;
      uint4* tp = P.sc->top + grp * 2 + lane;
      uint32_t exw = sb + OFF_EX + wt * 8 + w * 14336, exr = sb + OFF_EX + wt * 8 + 14336 - w * 14336;
      asm volatile("" : "+l"(sp), "+l"(tp), "+r"(exw), "+r"(exr)::"memory");
      mbar_wait(BAR(B_ATD));
      WG_WAIT(0);
      pin(acc);
      TT(16);
#pragma unroll
      for (int j = 0; j < 14; j++) sts64f(exw + j * 1024, acc[4 * j + 2], acc[4 * j + 3]);
      bar_sync(1, 256);
      TT(17);
      float sg[3][4] = {};
#pragma unroll
      for (int j = 0; j < 14; j++) {
        const float2 y = lds64f(exr + j * 1024);
        hh[j] = pack2(acc[4 * j] + y.x, acc[4 * j + 1] + y.y);
        mma1688(sg[j % 3], hh[j], bw[j], hh[j]);
      }
      const float e2 = sg[0][2] + sg[1][2] + sg[2][2], e3 = sg[0][3] + sg[1][3] + sg[2][3];
      const float sa = __shfl_sync(~0u, e2, c), sb2 = __shfl_sync(~0u, e3, c), da = __shfl_sync(~0u, e2, 4 + c), db = __shfl_sync(~0u, e3, 4 + c);
      if (c == (r >> 1))
        st_pkt(sp + quart * 64, __float_as_uint((r & 1) ? sb2 : sa), __float_as_uint((r & 1) ? sg[0][1] + sg[1][1] + sg[2][1] : sg[0][0] + sg[1][0] + sg[2][0]),
               __float_as_uint((r & 1) ? db : da), epoch);
      TS(8);
      float s0, u0, d0;
      {
        int n = 0;
        pause<D3>();
        uint4 q0 = ld_pkt(sp), q1 = ld_pkt(sp + 64), q2 = ld_pkt(sp + 128), q3 = ld_pkt(sp + 192);
        while (!__all_sync(~0u, q0.w == epoch && q1.w == epoch && q2.w == epoch && q3.w == epoch)) {
          spin_guard(n);
          pause<G3>();
          q0 = ld_pkt(sp); q1 = ld_pkt(sp + 64); q2 = ld_pkt(sp + 128); q3 = ld_pkt(sp + 192);
        }
        s0 = (__uint_as_float(q0.x) + __uint_as_float(q1.x)) + (__uint_as_float(q2.x) + __uint_as_float(q3.x));
        u0 = (__uint_as_float(q0.y) + __uint_as_float(q1.y)) + (__uint_as_float(q2.y) + __uint_as_float(q3.y));
        d0 = (__uint_as_float(q0.z) + __uint_as_float(q1.z)) + (__uint_as_float(q2.z) + __uint_as_float(q3.z));
        TT(18); TSV(19, n + 1);
      }
      const float mu = s0 * (1.f / D_), rs = ln_rstd(u0 * (1.f / D_) - mu * mu);
      const uint32_t mb = pack2(mu, mu);
      const uint32_t rr = pack2(0.f, (d0 - bf_lo(mb) * sw) * rs);
      const uint32_t key = (rr ^ (0x80000000u | (((int)rr >> 31) & 0x7fff0000u))) | (0xffffu - grow);
      if (c == 0) sts32(sb + OFF_MISC + 768 + lrow * 4, key);
      warp_arrive(BAR(B_KEY), lane);
      mbar_wait(BAR(B_KEY));
      const float2 kf2 = lds64f(sb + OFF_MISC + 768 + lane * 8);
      const uint32_t ka = max(__float_as_uint(kf2.x), __float_as_uint(kf2.y)), kb = min(__float_as_uint(kf2.x), __float_as_uint(kf2.y));
      G1 = __reduce_max_sync(~0u, ka);
      G2 = __reduce_max_sync(~0u, ka == G1 ? kb : ka);
      if (quart == 0 && tid < 2) st_pkt(tp, G1, G2, 0u, epoch);
      TS(9);
      BB(4);
      const uint32_t rh = pack2(rs, rs), rl = pack2(rs - bf_lo(rh), rs - bf_lo(rh));
#pragma unroll
      for (int j = 0; j < 14; j++) {
        const uint32_t d = hsub2(hh[j], mb);
        ln[j] = hfma2(d, rh, hmul2(d, rl));
      }
      if (key == G1 || key == G2) {
        uint4* cp = P.sc->cand + ((grp * 2 + (key == G2)) * 8 + 2 * quart) * 24 + c;
#pragma unroll
        for (int i = 0; i < 2; i++) {
          st_pkt(cp + 24 * i, ln[7 * i], ln[7 * i + 1], ln[7 * i + 2], epoch);
          st_pkt(cp + 24 * i + 4, ln[7 * i + 3], ln[7 * i + 4], ln[7 * i + 5], epoch);
          st_pkt(cp + 24 * i + 8, ln[7 * i + 6], 0u, 0u, epoch);
        }
#pragma unroll
        for (int i = 0; i < 2; i++) {
          st_pkt(cp + 24 * i + 12, hh[7 * i], hh[7 * i + 1], hh[7 * i + 2], epoch);
          st_pkt(cp + 24 * i + 16, hh[7 * i + 3], hh[7 * i + 4], hh[7 * i + 5], epoch);
          st_pkt(cp + 24 * i + 20, hh[7 * i + 6], 0u, 0u, epoch);
        }
      }
      TT(20);
#pragma unroll
      for (int j = 0; j < 14; j++) sts32(xr + 16 * j, hadd2(hh[j], ln[j]));
      bar_sync(1, 256);
    }
    const int row0 = rb * 128 + half * 64;
    const int c1 = 0xffff - (G1 & 0xffffu) - row0, c2 = 0xffff - (G2 & 0xffffu) - row0;
    char* const obase = (char*)P.out + row0 * 896 + quart * 224;
#define OUT_STORES() _Pragma("unroll") for (int k = 0; k < 4; k++) { \
      const int i = tid + 256 * k, row = (i * 4682) >> 16;       \
      if (i < 896 && row != c1 && row != c2) *(uint4*)(obase + row * 672 + i * 16) = lds128(sb + OFF_XR + i * 16); }
    TS(10);

    const bool ffn = bid < 112;
    uint32_t ag[14], au[14], ad[16];
    if (ffn) {
      mbar_wait(BAR(B_FFW));
      const uint32_t wa = sb + OFF_WG + (56 * warp + (lane & 7) + ((lane >> 4) & 1) * 8) * 32 + (((lane >> 3) ^ (lane >> 2)) & 1) * 16;
#pragma unroll
      for (int s = 0; s < 3; s++) {
        ldsm4t(ag[4 * s], ag[4 * s + 1], ag[4 * s + 2], ag[4 * s + 3], wa + s * 512);
        ldsm4t(au[4 * s], au[4 * s + 1], au[4 * s + 2], au[4 * s + 3], wa + 14336 + s * 512);
      }
      const uint32_t wb = sb + OFF_WG + (56 * warp + 48 + (lane & 7)) * 32 + (((lane >> 3) ^ (lane >> 2)) & 1) * 16;
      ldsm2t(ag[12], ag[13], wb);
      ldsm2t(au[12], au[13], wb + 14336);
      const uint32_t wc = sb + OFF_WD + ((lane & 7) + ((lane >> 4) & 1) * 8) * 912 + (56 * warp + ((lane >> 3) & 1) * 8) * 2;
#pragma unroll
      for (int m = 0; m < 4; m++) ldsm4t(ad[4 * m], ad[4 * m + 1], ad[4 * m + 2], ad[4 * m + 3], wc + m * 32);
    }
    {
    mbar_wait(BAR(B_TOP));
    const uint4 kk = lds128(sb + OFF_MISC);
    const uint32_t K1 = kk.x, K2 = kk.y, slot1 = kk.z, slot2 = kk.w;
    TS(11);
    if (ffn) {
      uint32_t b[7] = {0u, 0u, 0u, 0u, 0u, 0u, 0u};
      {
        const uint4* cp = P.sc->cand + (((lane & 4) ? slot2 : slot1) * 8 + warp) * 24 + c;
        int t0 = 0;
        while (true) {
          bool ok = true;
          if (lane < 8) {
            const uint4 q0 = ld_pkt(cp), q1 = ld_pkt(cp + 4), q2 = ld_pkt(cp + 8);
            ok = q0.w == epoch && q1.w == epoch && (q2.w ^ q2.y ^ q2.z) == epoch;
            b[0] = q0.x; b[1] = q0.y; b[2] = q0.z; b[3] = q1.x; b[4] = q1.y; b[5] = q1.z; b[6] = q2.x;
          }
          if (__all_sync(~0u, ok)) break;
          spin_guard(t0);
        }
      }
      TT(21);
      float cg[4] = {0.f, 0.f, 0.f, 0.f}, cu[4] = {0.f, 0.f, 0.f, 0.f};
#pragma unroll
      for (int s = 0; s < 3; s++) {
        mma16816(cg, ag[4 * s], ag[4 * s + 1], ag[4 * s + 2], ag[4 * s + 3], b[2 * s], b[2 * s + 1]);
        mma16816(cu, au[4 * s], au[4 * s + 1], au[4 * s + 2], au[4 * s + 3], b[2 * s], b[2 * s + 1]);
      }
      mma1688(cg, ag[12], ag[13], b[6]);
      mma1688(cu, au[12], au[13], b[6]);
      const uint32_t red = sb + OFF_RED;
      if (c == 0) {
        const uint32_t wa = red + w * 512 + r * 16 + v * 4;
#pragma unroll
        for (int i = 0; i < 4; i++) {
          sts32(wa + (i >> 1) * 128 + (i & 1) * 256, __float_as_uint(cg[i]));
          sts32(wa + 1024 + (i >> 1) * 128 + (i & 1) * 256, __float_as_uint(cu[i]));
        }
      }
      bar_sync(1, 256);
      TT(22);
      const uint32_t ra = red + lane * 16;
      const float4 g0 = lds128f(ra), g1 = lds128f(ra + 512), u0 = lds128f(ra + 1024), u1 = lds128f(ra + 1536);
      const float g = bfr(((g0.x + g0.y) + (g0.z + g0.w)) + ((g1.x + g1.y) + (g1.z + g1.w)));
      const float u = bfr(((u0.x + u0.y) + (u0.z + u0.w)) + ((u1.x + u1.y) + (u1.z + u1.w)));
      const float act = bfr(bfr(g * rcp(1.0f + ex2(-1.4426950408889634f * g))) * u);
      const int sl = (lane & 4) * 4 + 2 * c;
      const float x0 = __shfl_sync(~0u, act, sl), x1 = __shfl_sync(~0u, act, sl + 1);
      const float x2 = __shfl_sync(~0u, act, sl + 8), x3 = __shfl_sync(~0u, act, sl + 9);
      const uint32_t b0 = lane < 8 ? pack2(x0, x1) : 0u, b1 = lane < 8 ? pack2(x2, x3) : 0u;
      uint4* yp = P.sc->y + bid * 256 + warp * 32 + r;
#pragma unroll
      for (int m = 0; m < 4; m++) {
        float y[4] = {0.f, 0.f, 0.f, 0.f};
        mma16816(y, ad[4 * m], ad[4 * m + 1], ad[4 * m + 2], ad[4 * m + 3], b0, b1);
        if (c == 0)
          st_pkt(yp + m * 8, (__float_as_uint(y[0]) & ~1u) | (epoch & 1u), __float_as_uint(y[1]), __float_as_uint(y[2]), __float_as_uint(y[3]));
      }
    }
    TS(12);
    OUT_STORES()
    if (tid < 28) {
      const uint32_t g = tid < 14 ? G1 : G2;
      const int row = tid < 14 ? c1 : c2, j = tid < 14 ? tid : tid - 14;
      if (g != K1 && g != K2) *(uint4*)(obase + row * 896 + j * 16) = lds128(sb + OFF_XR + row * 224 + j * 16);
    }
    {
      const uint4* yp = P.sc->y + (warp * 14 + (lane >> 1)) * 256 + 2 * bid + (lane & 1);
      uint4 q = make_uint4(epoch, 0u, 0u, 0u);
      if (ffn) pause<D5>(); else pause<D5N>();
      if (lane < 28) q = ld_pkt(yp);
      int n = 0;
      while (!__all_sync(~0u, !((q.x ^ epoch) & 1))) {
        spin_guard(n);
        pause<G5>();
        if ((q.x ^ epoch) & 1) q = ld_pkt(yp);
      }
      TT(23);
      const float y0 = lane < 28 ? __uint_as_float(q.x) : 0.f, y1 = __uint_as_float(q.y), y2 = __uint_as_float(q.z), y3 = __uint_as_float(q.w);
      float z0 = (lane & 4) ? y2 : y0, z1 = (lane & 4) ? y3 : y1;
      z0 += __shfl_xor_sync(~0u, (lane & 4) ? y0 : y2, 4);
      z1 += __shfl_xor_sync(~0u, (lane & 4) ? y1 : y3, 4);
      float z = (lane & 2) ? z1 : z0;
      z += __shfl_xor_sync(~0u, (lane & 2) ? z0 : z1, 2);
      z += __shfl_xor_sync(~0u, z, 8);
      z += __shfl_xor_sync(~0u, z, 16);
      if (lane < 8) sts32(sb + OFF_RED2 + lane * 32 + warp * 4, __float_as_uint(z));
      __syncwarp();
      if (lane == 0) mbar_arrive(BAR(B_FIN));
    }
    }
    TS(13);
  } else {
    asm volatile("setmaxnreg.dec.sync.aligned.u32 56;");
    const int aw = warp - 8;
    mbar_init_e(BAR(B_XT) + 8 * aw, 1);
    asm volatile("fence.mbarrier_init.release.cluster;" ::: "memory");
    if (aw == 0) {
      mbar_expect_e(BAR(B_XT), 16384);
      tma2d_e(sb + OFF_X, &tm_x, 0, rb * 128, BAR(B_XT));
      TS(12);
    }
    bar_arrive(7, NTHR);
    bar_sync(3, 128);
    if (aw == 0) {
#pragma unroll
      for (int i = 1; i < 7; i++) {
        if (i & 1) mbar_expect_e(BAR(B_XT + (i + 1) / 2), 32768);
        tma2d_e(sb + OFF_X + i * 16384, &tm_x, i * 64, rb * 128, BAR(B_XT + (i + 1) / 2));
      }
      TS(13);
    }
    bar_sync(0, NTHR);
    if (aw == 0) {
      if (lane < 8) st_pkt(P.sc->flag + (rb * 8 + hg) * 8 + lane, 0u, 0u, 0u, 0u);
      __syncwarp();
#pragma unroll
      for (int i = 0; i < 8; i++) {
        if (i >= WDEPTH) mbar_wait(BAR(B_WKF + (i >= WDEPTH ? i - WDEPTH : 0)));
        mbar_expect_e(BAR(B_WKF + i), 14336);
        tma2d_e(sb + (i < 4 ? OFF_WK : OFF_WV) + (i & 3) * 14336, &tm_w, (i < 4 ? 448 : 896) + wcol, (i & 3) * 112, BAR(B_WKF + i));
      }
      TS(10);
    }
    uint32_t epoch;
    asm volatile("ld.relaxed.gpu.global.u32 %0, [%1];" : "=r"(epoch) : "l"(&P.sc->epoch) : "memory");
    if (warp == 9) {
      float s = 0.f;
#pragma unroll
      for (int i = 0; i < 7; i++) {
        const int j = lane + 32 * i - quart * 56;
        const uint32_t u = __ldg((const uint32_t*)P.wr + lane + 32 * i);
        s += bf_lo(u) + bf_hi(u);
        if (j >= 0 && j < 56) sts32(sb + OFF_MISC + 256 + j * 4, u);
      }
#pragma unroll
      for (int o = 16; o; o >>= 1) s += __shfl_xor_sync(~0u, s, o);
      if (lane == 0) sts32(sb + OFF_MISC + 16, __float_as_uint(s));
      sts64f(sb + OFF_MISC + 512 + lane * 8, __uint_as_float(0x3f803f80u), __uint_as_float(0x3f803f80u));
      warp_arrive(BAR(B_SW), lane);
    }
    if (aw == 0) {
      mbar_wait(BAR(B_XE));
      mbar_expect_e(BAR(B_WQF), 57344);
#pragma unroll
      for (int i = 0; i < 4; i++) {
        if (8 + i - QDEPTH < 8) mbar_wait(BAR(B_WKF + (8 + i - QDEPTH < 8 ? 8 + i - QDEPTH : 0)));
        tma2d_e(sb + OFF_WQ + i * 14336, &tm_w, wcol, i * 112, BAR(B_WQF));
      }
      TS(11);
    }
    if (warp == 10 && lane == 0) mbar_arrive(BAR(B_SW) + (epoch & P.zero));
    if (warp == 11) {
      mbar_wait(BAR(B_XE));
      const int grp = rb * 2 + half;
#pragma unroll
      for (int i = 0; i < 2; i++) st_pkt(P.sc->st + grp * 256 + quart * 64 + lane + 32 * i, 0u, 0u, 0u, 0u);
#pragma unroll
      for (int i = 0; i < 3; i++) {
        const int k = lane + 32 * i;
        st_pkt(P.sc->cand + ((grp * 2 + (k >= 48)) * 8 + 2 * quart) * 24 + (k >= 48 ? k - 48 : k), 0u, 0u, 0u, 0u);
      }
      if (quart == 0 && lane < 2) st_pkt(P.sc->top + grp * 2 + lane, 0u, 0u, 0u, 0u);
      if (bid < 112) {
#pragma unroll
        for (int i = 0; i < 8; i++) st_pkt(P.sc->y + bid * 256 + lane + 32 * i, epoch & 1u, 0u, 0u, 0u);
      }
      warp_arrive(BAR(B_SW), lane);
      if (rb < 2) {
        mbar_wait(BAR(B_KPD));
#pragma unroll 4
        for (int i = 0; i < 16; i++) sts128(sb + OFF_VA + 6 * 8192 + i * 512 + lane * 16, make_uint4(0u, 0u, 0u, 0u));
        fence_async();
      }
      warp_arrive(BAR(B_VB + 4), lane);
    }
    __syncwarp();
    epoch += 1;
    const uint32_t par = epoch & 1;
    uint4* const gp = P.sc->kv + (rb * 8 + hg) * 2048;
    const uint4* const g1 = gp - 8 * 2048;
    const uint4* const g2 = rb > 1 ? g1 - 8 * 2048 : g1;
#define IMG(n, slot) (sb + ((n) >= 2 ? OFF_VA + (slot) * 8192 : OFF_KA + (slot) * 7168))
#define FETCH(n) { \
      const uint32_t by = (n) >= 2 ? 8192 : 7168; \
      mbar_expect_e(BAR(B_FB) + 8 * (n), 2 * by); \
      bulk_g2s_e(IMG(n, 3 - ((n) & 1)), g1 + (n) * 512, by, BAR(B_FB) + 8 * (n)); \
      bulk_g2s_e(IMG(n, 1 - ((n) & 1)), g2 + (n) * 512, by, BAR(B_FB) + 8 * (n)); }
    uint4* const fl = P.sc->flag + (rb * 8 + hg) * 8;
    if (aw == 0) {
#pragma unroll
      for (int n = 0; n < 4; n++) {
        mbar_wait(BAR((n >= 2 ? B_VB : B_KB) + 5 - (n & 1)));
        if (lane == 2 * n) st_pkt(fl + 2 * n, 0u, 0u, 0u, epoch);
        __syncwarp();
        bulk_s2g_e(gp + n * 512, IMG(n, 5 - (n & 1)), n >= 2 ? 8192 : 7168);
      }
      asm volatile("cp.async.bulk.commit_group;" ::: "memory");
    } else if (rb) {
#pragma unroll 1
      for (int n = warp - 9; n < 4; n += 3) {
        if (lane < 2) {
          const uint4* fp = fl + 2 * n - ((lane && rb > 1) ? 128 : 64);
          int k = 0;
          while (ld_pkt(fp).w != epoch) spin_guard(k);
        }
        __syncwarp();
        if (n == 2) mbar_wait(BAR(B_KPD));
        if (n == 0) mbar_wait(BAR(B_XE));
        const uint32_t lo = lane * 32 + (lane & 4) * 4, i1 = IMG(n, 3 - (n & 1)) + lo, i2 = IMG(n, 1 - (n & 1)) + lo;
        int tries = 0;
        while (true) {
          FETCH(n)
          mbar_wait_par(BAR(B_FB) + 8 * n, tries & 1);
          uint32_t bad = 0;
#pragma unroll
          for (int k = 0; k < 8; k++) {
            const uint32_t o = (k < 7 || n >= 2) ? k * 1024 : 0;
            bad |= (lds32(i1 + o) ^ par) | (lds32(i2 + o) ^ par);
          }
          if (__all_sync(~0u, !(bad & 1))) break;
          spin_guard(tries);
        }
        if (lane == 0) {
          const uint32_t hb = BAR(n >= 2 ? B_VB : B_KB) + 8 - 8 * (n & 1);
          mbar_arrive(hb + 16);
          mbar_arrive(hb);
        }
      }
    }
    if (aw == 0) {
      mbar_wait(BAR(B_QPD));
      if (rb) mbar_wait(BAR(B_VB + 2));
#pragma unroll
      for (int i = 0; i < 2; i++) {
        mbar_expect_e(BAR(B_WOF + i), 57344);
        tma2d_e(sb + (i ? OFF_WV : OFF_WQ), &tm_wo, quart * 112, 224 * i, BAR(B_WOF + i));
        tma2d_e(sb + (i ? OFF_WV : OFF_WQ) + 28672, &tm_wo, quart * 112 + 64, 224 * i, BAR(B_WOF + i));
      }
      mbar_expect_e(BAR(B_XRF), 14336);
      tma2d_e(sb + OFF_XR, &tm_xr, quart * 112, rb * 128 + half * 64, BAR(B_XRF));
      l2_prefetch_e((const char*)P.wg + bid * 12544, 12544);
      l2_prefetch_e((const char*)P.wu + bid * 12544, 12544);
      l2_prefetch_e((const char*)P.wd + bid * 12544, 12544);
      if (bid < 112) {
        mbar_wait(BAR(FFAT == 0 ? B_ATD : FFAT == 1 ? B_OGD : B_KEY));
        mbar_expect_e(BAR(B_FFW), 43008);
        tma2d_e(sb + OFF_WG, &tm_g, bid * 16, 0, BAR(B_FFW));
        tma2d_e(sb + OFF_WG + 7168, &tm_g, bid * 16, 224, BAR(B_FFW));
        tma2d_e(sb + OFF_WU, &tm_u, bid * 16, 0, BAR(B_FFW));
        tma2d_e(sb + OFF_WU + 7168, &tm_u, bid * 16, 224, BAR(B_FFW));
        mbar_wait(BAR(B_ATD));
#pragma unroll 1
        for (int i = 0; i < 16; i++) bulk_g2s_e(sb + OFF_WD + i * 912, (const char*)P.wd + bid * 14336 + i * 896, 896, BAR(B_FFW));
      }
      asm volatile("cp.async.bulk.wait_group 0;" ::: "memory");
    } else if (warp == 10) {
      const int e = (lane >> 1) & 3, tok = e & 1;
      const int cl = 16 * ((bid >> 2) & 3) + ((2 * bid) & 7) + (lane & 1) + 8 * (e >> 1), tile = cl >> 3;
      const bool val = lane < 8 && cl < 56;
      {
      mbar_wait(BAR(B_KEY));
      uint32_t K1, K2, slot1, slot2;
      global_top2(P.sc->top + 2 * lane, epoch, K1, K2, slot1, slot2);
      if (lane == 0) {
        sts128(sb + OFF_MISC, make_uint4(K1, K2, slot1, slot2));
        mbar_arrive(BAR(B_TOP));
        if (bid == 0) asm volatile("st.relaxed.gpu.global.u32 [%0], %1;" ::"l"(&P.sc->epoch), "r"(epoch) : "memory");
      }
      const uint32_t key = tok ? K2 : K1, ob = key >> 16;
      const float rv = __uint_as_float(((ob & 0x8000u) ? (ob ^ 0x8000u) : (~ob & 0xffffu)) << 16);
      const float sg = bfr(rcp(1.0f + ex2(-1.4426950408889634f * rv)));
      float lnv = 0.f, hv = 0.f;
      int n = 0;
      if (val) {
        const uint4* cp = P.sc->cand + ((tok ? slot2 : slot1) * 8 + (bid >> 4)) * 24 + (tile / 3) * 4 + ((cl & 7) >> 1);
        while (true) {
          const uint4 q0 = ld_pkt(cp), q1 = ld_pkt(cp + 12);
          const int sl = tile % 3;
          const uint32_t a = sl == 0 ? q0.x : sl == 1 ? q0.y : q0.z, b = sl == 0 ? q1.x : sl == 1 ? q1.y : q1.z;
          lnv = (cl & 1) ? bf_hi(a) : bf_lo(a);
          hv = (cl & 1) ? bf_hi(b) : bf_lo(b);
          if (q0.w == epoch && q1.w == epoch) break;
          spin_guard(n);
        }
      }
      __nv_bfloat16* op = P.out + (0xffff - (key & 0xffffu)) * D_ + 56 * (bid >> 4) + cl;
      asm volatile("" : "+l"(op), "+f"(lnv), "+f"(hv)::"memory");
      mbar_wait(BAR(B_FIN));
      const float4 a = lds128f(sb + OFF_RED2 + (lane & 7) * 32), b = lds128f(sb + OFF_RED2 + (lane & 7) * 32 + 16);
      const float z = ((a.x + a.y) + (a.z + a.w)) + ((b.x + b.y) + (b.z + b.w));
      if (val) *op = __float2bfloat16(hv + bfr(lnv + bfr(bfr(z) * sg)));
      }
    }
  }
  TS_DUMP();
#undef BAR
}

typedef CUresult (*EncodeFn)(CUtensorMap*, CUtensorMapDataType, cuuint32_t, void*, const cuuint64_t*, const cuuint64_t*,
                             const cuuint32_t*, const cuuint32_t*, CUtensorMapInterleave, CUtensorMapSwizzle,
                             CUtensorMapL2promotion, CUtensorMapFloatOOBfill);

void make_map(EncodeFn enc, CUtensorMap* m, const void* p, int cols, int rows, int bc, int br, CUtensorMapSwizzle sw) {
  cuuint64_t gd[2] = {(cuuint64_t)cols, (cuuint64_t)rows};
  cuuint64_t gs[1] = {(cuuint64_t)cols * 2};
  cuuint32_t bx[2] = {(cuuint32_t)bc, (cuuint32_t)br};
  cuuint32_t es[2] = {1, 1};
  enc(m, CU_TENSOR_MAP_DATA_TYPE_BFLOAT16, 2, (void*)p, gd, gs, bx, es, CU_TENSOR_MAP_INTERLEAVE_NONE, sw,
      CU_TENSOR_MAP_L2_PROMOTION_L2_128B, CU_TENSOR_MAP_FLOAT_OOB_FILL_NONE);
}

}

extern "C" void kernel_launch(void* const* d_in, const int* in_sizes, int n_in, void* d_out, int out_size) {
  (void)in_sizes; (void)n_in; (void)out_size;
  static EncodeFn enc = nullptr;
  static Scratch* scratch = nullptr;
  if (!enc) {
    void* fn = nullptr;
    cudaDriverEntryPointQueryResult qr;
    cudaGetDriverEntryPoint("cuTensorMapEncodeTiled", &fn, cudaEnableDefault, &qr);
    enc = (EncodeFn)fn;
    cudaGetSymbolAddress((void**)&scratch, g_scratch);
    cudaFuncSetAttribute(fused_kernel, cudaFuncAttributeMaxDynamicSharedMemorySize, SMEM_BYTES);
  }
  CUtensorMap tx, tw, two, txr, tg, tu;
  make_map(enc, &txr, d_in[0], D_, S_, 112, 64, CU_TENSOR_MAP_SWIZZLE_NONE);
  make_map(enc, &tx, d_in[0], D_, S_, 64, 128, CU_TENSOR_MAP_SWIZZLE_128B);
  make_map(enc, &tw, d_in[1], 3 * D_, D_, 64, 112, CU_TENSOR_MAP_SWIZZLE_128B);
  make_map(enc, &two, d_in[2], D_, D_, 64, 224, CU_TENSOR_MAP_SWIZZLE_128B);
  make_map(enc, &tg, d_in[5], F_, D_, 16, 224, CU_TENSOR_MAP_SWIZZLE_32B);
  make_map(enc, &tu, d_in[6], F_, D_, 16, 224, CU_TENSOR_MAP_SWIZZLE_32B);
  Params p;
  p.wqkv = (const __nv_bfloat16*)d_in[1];
  p.x = (const __nv_bfloat16*)d_in[0];
  p.wr = (const __nv_bfloat16*)d_in[4];
  p.wg = (const __nv_bfloat16*)d_in[5];
  p.wu = (const __nv_bfloat16*)d_in[6];
  p.wd = (const __nv_bfloat16*)d_in[7];
  p.out = (__nv_bfloat16*)d_out;
  p.sc = scratch;
  p.zero = 0;
  fused_kernel<<<NCTA, NTHR, SMEM_BYTES>>>(p, tx, tw, two, txr, tg, tu);
}
```
